```python
import torch

def _softmax(x, axis=-1):
    return torch.softmax(x, dim=axis)
def _gelu(x):
    return torch.nn.functional.gelu(x, approximate="tanh")
def _silu(x):
    return torch.nn.functional.silu(x)
def _sigmoid(x):
    return torch.sigmoid(x)
def _layernorm(x, axis=-1, eps=1e-5):
    m = x.mean(dim=axis, keepdim=True)
    v = x.var(dim=axis, keepdim=True, unbiased=False)
    return (x - m) / torch.sqrt(v + eps)
def _scatter_add(tgt, idx, src, axis=0):
    return tgt.clone().index_add_(axis, idx, src)
def _segment_sum(src, seg, n):
    out = torch.zeros((n,) + src.shape[1:], dtype=src.dtype)
    return out.index_add_(0, seg, src)
def _pad(x, pw):
    flat = tuple(v for pair in reversed(pw) for v in pair)
    return torch.nn.functional.pad(x, flat)

kernel_name = 'gated_mix__sliding_block_cached__glu_gated_reglu__decode'

def setup_inputs():

    _w = (lambda a: (lambda t: t.to(torch.bfloat16) if t.is_floating_point() else t)(torch.as_tensor(a)))
    def _A_setup():
        B, Sq, D = 1, 1, 640
        Hq, Hkv, Sk, Dh = 32, 32, 32768, 192
        assert Hq % Hkv == 0, (Hq, Hkv)
        return {
            "x": _w((lambda *s: torch.randn(*s, dtype=torch.bfloat16) * 0.05)(B, Sq, D)),
            "k_cache": _w((lambda *s: torch.randn(*s, dtype=torch.bfloat16) * 6.4)(B, Hkv, Sk, Dh)),
            "v_cache": _w((lambda *s: torch.randn(*s, dtype=torch.bfloat16) * 0.05)(B, Hkv, Sk, Dh)),
            "wq": _w((lambda *s: torch.randn(*s, dtype=torch.bfloat16) * 6.4)(D, Hq * Dh) * (D ** -0.5)),
            "wo": _w((lambda *s: torch.randn(*s, dtype=torch.bfloat16) * 0.05)(Hq * Dh, D) * ((Hq * Dh) ** -0.5)),
        }
    _A_in = _A_setup()

    def _B_setup():
        B, S, D, F = 1, 1, 640, 1536
        return {
            "x": _w((lambda *s: torch.randn(*s, dtype=torch.bfloat16) * 0.05)(B, S, D)),
            "W_gate": _w((lambda *s: torch.randn(*s, dtype=torch.bfloat16) * 0.4)(D, F) * (2.0 / D) ** 0.5),
            "W_up": _w((lambda *s: torch.randn(*s, dtype=torch.bfloat16) * 0.4)(D, F) * (2.0 / D) ** 0.5),
            "W_down": _w((lambda *s: torch.randn(*s, dtype=torch.bfloat16) * 0.4)(F, D) * (1.0 / F) ** 0.5),
        }
    _B_in = _B_setup()

    return {
        "A_x": _A_in["x"],
        "A_k_cache": _A_in["k_cache"],
        "A_v_cache": _A_in["v_cache"],
        "A_wq": _A_in["wq"],
        "A_wo": _A_in["wo"],
        "B_x": _B_in["x"],
        "B_W_gate": _B_in["W_gate"],
        "B_W_up": _B_in["W_up"],
        "B_W_down": _B_in["W_down"],
        "gate_w": _w((lambda *s: torch.randn(*s, dtype=torch.bfloat16) * 0.1)(640) * 16.0),
    }

def reference(A_x, A_k_cache, A_v_cache, A_wq, A_wo, B_x, B_W_gate, B_W_up, B_W_down, gate_w):
    def _A_ref(x, k_cache, v_cache, wq, wo):
        B, Sq, D = x.shape
        Hq, Dh = 32, 192
        Hkv, Sk = k_cache.shape[1], k_cache.shape[2]
        W = min(4096, max(256, Sk // 4))
        rep = Hq // Hkv
        q = (lambda x, *d: x.permute(*d))((x @ wq).reshape(B, Sq, Hq, Dh), 0, 2, 1, 3)
        k = (lambda x, n, axis: torch.repeat_interleave(x, n, dim=axis))(k_cache[:, :, Sk - W:, :], rep, axis=1)
        v = (lambda x, n, axis: torch.repeat_interleave(x, n, dim=axis))(v_cache[:, :, Sk - W:, :], rep, axis=1)
        scores = torch.einsum("bhqd,bhkd->bhqk", q, k) * (Dh ** -0.5)
        p = _softmax(scores, axis=-1)
        o = torch.einsum("bhqk,bhkd->bhqd", p, v)
        return (lambda x, *d: x.permute(*d))(o, 0, 2, 1, 3).reshape(B, Sq, Hq * Dh) @ wo

    def _B_ref(x, W_gate, W_up, W_down):
        gate = torch.einsum("bsd,df->bsf", x, W_gate)
        up = torch.einsum("bsd,df->bsf", x, W_up)
        gate = gate * (lambda x, dt: x.to(dt))(gate > 0, gate.dtype)
        h = gate * up
        return torch.einsum("bsf,fd->bsd", h, W_down)

    x = A_x
    g = _sigmoid((x * gate_w).sum(-1, keepdims=True))
    a = _A_ref(x, A_k_cache, A_v_cache, A_wq, A_wo)
    b = _B_ref(x, B_W_gate, B_W_up, B_W_down)
    return g * a + (1 - g) * b
```

```cpp
#include <cuda_runtime.h>
#include <cuda_bf16.h>
#include <cuda.h>
#include <stdint.h>

namespace {

constexpr int kD = 640;
constexpr int kH = 32;
constexpr int kDh = 192;
constexpr int kSk = 32768;
constexpr int kW = 4096;
constexpr int kF = 1536;
constexpr int kSplit = 4;
constexpr int kCTAs = kH * kSplit;
constexpr int kCW = 8;
constexpr int kThreads = kCW * 32 + 64;
constexpr int kTileKeys = 64;
constexpr int kRowB = kDh * 2;
constexpr int kTileB = kTileKeys * kRowB;
constexpr int kStages = 8;
constexpr int kKVTiles = kW / kSplit / kTileKeys;
constexpr int kOutRowB = kD * 2;
constexpr int kFC = kF / kCTAs;
constexpr int kOC = kDh / kSplit;
constexpr int kXR = kD / kSplit;
constexpr int kFR = kD / 8;
constexpr int kTQ = 0;
constexpr int kTK = 3;
constexpr int kTF = kTK + kKVTiles;
constexpr int kTV = kTF + 2;
constexpr int kTD = kTV + kKVTiles;
constexpr int kTO = kTD + 1;
constexpr int kNumTiles = kTO + 3;
constexpr int kSlots = (kD + 2) / 3;
constexpr unsigned kSpinLimit = 1u << 24;
#define WINDOW 53248
#define PREWRITE 1
#define HELPER_SLEEP 4000
#define ACCSTRIDE 16
constexpr uint32_t kWindow = WINDOW;
constexpr int kAccStride = ACCSTRIDE;

constexpr int kScQ = 128, kScF = 152, kScStride = 168;

struct Smem {
    alignas(128) unsigned char ring[kStages][kTileB];
    alignas(16) float red[kCW * kDh];
    alignas(16) float ored[3 * kD + 8];
    alignas(16) float sc[kCW][kScStride];
    alignas(16) float q[kDh];
    alignas(16) float coef[3][20];
    float wmax[kCW];
    float wsum[kCW];
    float oscale;
    unsigned tag;
    alignas(8) unsigned long long full[kStages];
    alignas(8) unsigned long long empty[kStages];
};

__device__ unsigned g_mail[3 * kCTAs * kDh];
__device__ unsigned g_stat[kCTAs * 8];
__device__ float4 g_acc[(kSlots / 2 + 1) * kAccStride];
__device__ unsigned g_epoch;

#define TSTAMP(i) do {} while (0)

__device__ __forceinline__ uint32_t s2u(const void* p) { return (uint32_t)__cvta_generic_to_shared(p); }

__device__ __forceinline__ void mbar_init(uint32_t bar, uint32_t cnt) {
    asm volatile("mbarrier.init.shared::cta.b64 [%0], %1;" ::"r"(bar), "r"(cnt) : "memory");
}
__device__ __forceinline__ void mbar_expect_tx(uint32_t bar, uint32_t bytes) {
    asm volatile("mbarrier.arrive.expect_tx.shared::cta.b64 _, [%0], %1;" ::"r"(bar), "r"(bytes) : "memory");
}
__device__ __forceinline__ void mbar_arrive(uint32_t bar) {
    asm volatile("mbarrier.arrive.shared::cta.b64 _, [%0];" ::"r"(bar) : "memory");
}
__device__ __forceinline__ void mbar_wait(uint32_t bar, uint32_t parity) {
    asm volatile("{\n.reg .pred p;\n.reg .u32 n;\nmov.u32 n, 0;\n"
                 "WL:\nmbarrier.try_wait.parity.shared::cta.b64 p, [%0], %1;\n@p bra WD;\n"
                 "add.u32 n, n, 1;\nsetp.lt.u32 p, n, %2;\n@p bra WL;\ntrap;\nWD:\n}"
                 ::"r"(bar), "r"(parity), "n"(kSpinLimit) : "memory");
}
#define EVICT_FIRST 1
__device__ __forceinline__ void bulk_g2s(uint32_t dst, const void* src, uint32_t bytes, uint32_t bar, uint64_t pol) {
    asm volatile("cp.async.bulk.shared::cluster.global.mbarrier::complete_tx::bytes.L2::cache_hint [%0], [%1], %2, [%3], %4;"
                 ::"r"(dst), "l"(src), "r"(bytes), "r"(bar), "l"(pol) : "memory");
}
__device__ __forceinline__ void tma_2d(uint32_t dst, const CUtensorMap* map, int col, int row, uint32_t bar, uint64_t pol) {
    asm volatile("cp.async.bulk.tensor.2d.shared::cluster.global.mbarrier::complete_tx::bytes.L2::cache_hint [%0], [%1, {%3, %4}], [%2], %5;"
                 ::"r"(dst), "l"(map), "r"(bar), "r"(col), "r"(row), "l"(pol) : "memory");
}
__device__ __forceinline__ uint4 ldg128(const void* p) {
    uint4 v;
    asm volatile("ld.global.nc.v4.u32 {%0,%1,%2,%3}, [%4];" : "=r"(v.x), "=r"(v.y), "=r"(v.z), "=r"(v.w) : "l"(p));
    return v;
}
__device__ __forceinline__ uint4 lds128(uint32_t a) {
    uint4 v;
    asm volatile("ld.shared.v4.u32 {%0,%1,%2,%3}, [%4];" : "=r"(v.x), "=r"(v.y), "=r"(v.z), "=r"(v.w) : "r"(a));
    return v;
}
__device__ __forceinline__ void word_st(unsigned* p, float v, unsigned tag) {
    asm volatile("st.relaxed.gpu.global.u32 [%0], %1;" ::"l"(p), "r"((__float_as_uint(v) & ~3u) | tag) : "memory");
}
template <int N, int W>
__device__ __forceinline__ void word_wait(const unsigned* const (&p)[N], unsigned tag, float (&v)[N * W]) {
    unsigned n = 0;
#pragma unroll 1
    while (true) {
        unsigned r[N * W];
#pragma unroll
        for (int j = 0; j < N; j++) {
            if (W == 1) asm volatile("ld.relaxed.gpu.global.u32 %0, [%1];" : "=r"(r[j]) : "l"(p[j]) : "memory");
            else asm volatile("ld.relaxed.gpu.global.v2.u32 {%0,%1}, [%2];" : "=r"(r[j * W]), "=r"(r[j * W + W - 1]) : "l"(p[j]) : "memory");
        }
        unsigned bad = 0;
#pragma unroll
        for (int j = 0; j < N * W; j++) { bad |= (r[j] ^ tag) & 3u; v[j] = __uint_as_float(r[j] & ~3u); }
        if (bad == 0) break;
        if (++n > kSpinLimit) __trap();
    }
}
__device__ __forceinline__ float4 atom_add4(float4* p, float a, float b, float c, float d) {
    float4 r;
    asm volatile("atom.relaxed.gpu.global.add.v4.f32 {%0,%1,%2,%3}, [%4], {%5,%6,%7,%8};"
                 : "=f"(r.x), "=f"(r.y), "=f"(r.z), "=f"(r.w) : "l"(p), "f"(a), "f"(b), "f"(c), "f"(d) : "memory");
    return r;
}
__device__ __forceinline__ void cbar() { asm volatile("bar.sync 1, 256;" ::: "memory"); }
__device__ __forceinline__ void bar_sync(int id, int n) { asm volatile("bar.sync %0, %1;" ::"r"(id), "r"(n) : "memory"); }
__device__ __forceinline__ void bar_arrive(int id, int n) { asm volatile("bar.arrive %0, %1;" ::"r"(id), "r"(n) : "memory"); }

__device__ __forceinline__ float bf_lo(uint32_t w) { return __uint_as_float(w << 16); }
__device__ __forceinline__ float bf_hi(uint32_t w) { return __uint_as_float(w & 0xffff0000u); }
__device__ __forceinline__ float bfr(float v) { return __bfloat162float(__float2bfloat16_rn(v)); }

__device__ __forceinline__ void axpy8(float* acc, float c, const uint4& v) {
    acc[0] = fmaf(c, bf_lo(v.x), acc[0]); acc[1] = fmaf(c, bf_hi(v.x), acc[1]);
    acc[2] = fmaf(c, bf_lo(v.y), acc[2]); acc[3] = fmaf(c, bf_hi(v.y), acc[3]);
    acc[4] = fmaf(c, bf_lo(v.z), acc[4]); acc[5] = fmaf(c, bf_hi(v.z), acc[5]);
    acc[6] = fmaf(c, bf_lo(v.w), acc[6]); acc[7] = fmaf(c, bf_hi(v.w), acc[7]);
}
__device__ __forceinline__ float dot8(const float* q, const uint4& v) {
    float a = q[0] * bf_lo(v.x), b = q[1] * bf_hi(v.x);
    a = fmaf(q[2], bf_lo(v.y), a); b = fmaf(q[3], bf_hi(v.y), b);
    a = fmaf(q[4], bf_lo(v.z), a); b = fmaf(q[5], bf_hi(v.z), b);
    a = fmaf(q[6], bf_lo(v.w), a); b = fmaf(q[7], bf_hi(v.w), b);
    return a + b;
}

__device__ __forceinline__ uint32_t tile_bytes(int t) {
    uint32_t b = kTileB;
    if (t == kTQ + 2) b = 32 * kRowB;
    if (t == kTF || t == kTF + 1 || t == kTD || t == kTO + 2) b = 40 * kRowB;
    if (t == kTO || t == kTO + 1) b = 18 * kOutRowB;
    return b;
}
static_assert(40 * kRowB == 12 * kOutRowB, "");

struct Params {
    CUtensorMap tq;
    CUtensorMap tg;
    CUtensorMap tu;
    const __nv_bfloat16* x;
    const unsigned char* k;
    const unsigned char* v;
    const unsigned char* wo;
    const unsigned char* wd;
    const __nv_bfloat16* gate_w;
    __nv_bfloat16* out;
};

__global__ void __launch_bounds__(kThreads, 1) fused_decode_kernel(const __grid_constant__ Params p) {
    extern __shared__ __align__(128) unsigned char smem_raw[];
    Smem& sm = *reinterpret_cast<Smem*>(smem_raw);
    const int tid = threadIdx.x;
    const int lane = tid & 31;
    const int warp = tid >> 5;
    const int cta = blockIdx.x;
    const int h = cta >> 2;
    const int s = cta & 3;
    const uint32_t ring0 = s2u(&sm.ring[0][0]);
    const uint32_t full0 = s2u(&sm.full[0]);
    const uint32_t empty0 = s2u(&sm.empty[0]);

    if (warp == kCW) {
        uint64_t pol;
        asm volatile("createpolicy.fractional.L2::evict_first.b64 %0, 1.0;" : "=l"(pol));
        if (lane == 0) {
            TSTAMP(0);
#pragma unroll
            for (int i = 0; i < kStages; i++) { mbar_init(full0 + 8 * i, 1); mbar_init(empty0 + 8 * i, kCW); }
            asm volatile("fence.mbarrier_init.release.cluster;" ::: "memory");
            asm volatile("fence.proxy.async.shared::cta;" ::: "memory");
#pragma unroll
            for (int i = 0; i < 2; i++) {
                mbar_expect_tx(full0 + 8 * i, kTileB);
                tma_2d(ring0 + i * kTileB, &p.tq, h * kDh, s * kXR + i * 64, full0 + 8 * i, pol);
                tma_2d(ring0 + i * kTileB + 32 * kRowB, &p.tq, h * kDh, s * kXR + i * 64 + 32, full0 + 8 * i, pol);
            }
            TSTAMP(1);
        }
        __syncwarp();
        bar_arrive(2, kThreads);
        if (lane == 0) {
            const size_t kvoff = ((size_t)h * kSk + (kSk - kW) + s * kTileKeys) * kRowB;
            const unsigned char* src = p.k + kvoff;
            uint32_t step = kSplit * kTileB;
            uint32_t inflight = 2 * kTileB;
            int landed = 0;
#pragma unroll 1
            for (int t = 2; t < kNumTiles; t++) {
                const uint32_t bytes = tile_bytes(t);
                const uint32_t st = t % kStages;
                if (t == kTV) src = p.v + kvoff;
                if (t == kTD) src = p.wd + (size_t)cta * (kFC * kOutRowB);
                if (t == kTO) { src = p.wo + (size_t)cta * (kOC * kOutRowB); step = 18 * kOutRowB; }
                if (t >= kStages) mbar_wait(empty0 + 8 * st, ((t / kStages) - 1) & 1);
                inflight += bytes;
                while (inflight > kWindow) {
                    mbar_wait(full0 + 8 * (landed % kStages), (landed / kStages) & 1);
                    TSTAMP(16 + landed);
                    inflight -= tile_bytes(landed);
                    landed++;
                }
                mbar_expect_tx(full0 + 8 * st, bytes);
                if (t == kTQ + 2) {
                    tma_2d(ring0 + st * kTileB, &p.tq, h * kDh, s * kXR + 128, full0 + 8 * st, pol);
                } else if (t == kTF || t == kTF + 1) {
                    tma_2d(ring0 + st * kTileB, cta < 64 ? &p.tg : &p.tu, ((cta >> 3) & 7) * kDh,
                           (cta & 7) * kFR + (t - kTF) * 40, full0 + 8 * st, pol);
                } else {
                    bulk_g2s(ring0 + st * kTileB, src, bytes, full0 + 8 * st, pol);
                    src += step;
                }
            }
        }
        return;
    }

    if (warp == kCW + 1) {
        unsigned e = 0;
        if (lane == 0) asm volatile("ld.relaxed.gpu.global.u32 %0, [%1];" : "=r"(e) : "l"(&g_epoch) : "memory");
        uint4 gx[3], gw[3];
#pragma unroll
        for (int j = 0; j < 3; j++) {
            gx[j] = gw[j] = make_uint4(0, 0, 0, 0);
            if (lane + 32 * j < kD / 8) {
                gx[j] = ldg128(reinterpret_cast<const unsigned char*>(p.x) + (lane + 32 * j) * 16);
                gw[j] = ldg128(reinterpret_cast<const unsigned char*>(p.gate_w) + (lane + 32 * j) * 16);
            }
        }
        if (lane < 8) word_st(&g_stat[cta * 8 + lane], 0.f, 0u);
        const unsigned tag = __shfl_sync(0xffffffffu, e, 0) % 3u + 1u;
        if (lane == 0) sm.tag = tag;
        bar_arrive(2, kThreads);
        float z = 0.f;
#pragma unroll
        for (int j = 0; j < 3; j++) {
            z += bfr(bf_lo(gx[j].x) * bf_lo(gw[j].x)) + bfr(bf_hi(gx[j].x) * bf_hi(gw[j].x));
            z += bfr(bf_lo(gx[j].y) * bf_lo(gw[j].y)) + bfr(bf_hi(gx[j].y) * bf_hi(gw[j].y));
            z += bfr(bf_lo(gx[j].z) * bf_lo(gw[j].z)) + bfr(bf_hi(gx[j].z) * bf_hi(gw[j].z));
            z += bfr(bf_lo(gx[j].w) * bf_lo(gw[j].w)) + bfr(bf_hi(gx[j].w) * bf_hi(gw[j].w));
        }
#pragma unroll
        for (int o = 16; o > 0; o >>= 1) z += __shfl_xor_sync(0xffffffffu, z, o);
        const float gate = bfr(1.0f / (1.0f + __expf(-bfr(z))));

        bar_sync(3, 288);
        {
            float m = sm.wmax[lane & 7], l = sm.wsum[lane & 7];
#pragma unroll
            for (int o = 4; o > 0; o >>= 1) {
                m = fmaxf(m, __shfl_xor_sync(0xffffffffu, m, o));
                l += __shfl_xor_sync(0xffffffffu, l, o);
            }
            if (lane < 2) word_st(&g_stat[cta * 8 + lane], lane ? l : m, tag);
            __nanosleep(HELPER_SLEEP);
            const unsigned* const ps[1] = {&g_stat[(h * kSplit + (lane & 3)) * 8]};
            float v[2];
            word_wait<1, 2>(ps, tag, v);
            float M = fmaxf(v[0], __shfl_xor_sync(0xffffffffu, v[0], 1));
            M = fmaxf(M, __shfl_xor_sync(0xffffffffu, M, 2));
            const float w = __expf(v[0] - M);
            float L = w * v[1];
            L += __shfl_xor_sync(0xffffffffu, L, 1);
            L += __shfl_xor_sync(0xffffffffu, L, 2);
            if (lane == s) sm.oscale = w / L;
        }
        {
            const int mtx = lane >> 4, rb = (lane >> 1) & 7, half = lane & 1;
            const unsigned* src = &g_mail[(kCTAs + (mtx * 8 + (cta >> 4)) * 8 + rb) * kDh + (cta & 15) * kFC + half * 6];
            const unsigned* const ps[3] = {src, src + 2, src + 4};
            float v[6];
            word_wait<3, 2>(ps, tag, v);
            const float omg = bfr(1.0f - gate);
#pragma unroll
            for (int j = 0; j < 6; j++) {
                v[j] += __shfl_xor_sync(0xffffffffu, v[j], 2);
                v[j] += __shfl_xor_sync(0xffffffffu, v[j], 4);
                v[j] += __shfl_xor_sync(0xffffffffu, v[j], 8);
                const float gt = bfr(v[j]);
                const float up = __shfl_xor_sync(0xffffffffu, gt, 16);
                const int f = half * 6 + j;
                if (lane < 2) sm.coef[f >> 2][16 + (f & 3)] = bfr((gt > 0.f ? gt : gt * 0.f) * up) * omg;
            }
        }
        bar_arrive(4, 288);
        bar_sync(5, 288);
        if (lane < 24) {
            const unsigned* src = &g_mail[(2 * kCTAs + h * kSplit) * kDh + s * kOC + lane * 2];
            const unsigned* const ps[3] = {src + ((s + 1) & 3) * kDh, src + ((s + 2) & 3) * kDh, src + ((s + 3) & 3) * kDh};
            const float2 own = *reinterpret_cast<const float2*>(&sm.q[s * kOC + lane * 2]);
            const int d = lane * 2, tl = d / 18, r = d - tl * 18;
            float* dst = tl < 2 ? &sm.coef[r / 6][tl * 6 + r % 6] : &sm.coef[r >> 2][12 + (r & 3)];
            float v[6];
            word_wait<3, 2>(ps, tag, v);
            *reinterpret_cast<float2*>(dst) = make_float2(bfr((own.x + v[0]) + (v[2] + v[4])) * gate,
                                                          bfr((own.y + v[1]) + (v[3] + v[5])) * gate);
        }
        if (lane == 0) TSTAMP(8);
        bar_arrive(6, 288);
        return;
    }

    const int g = lane >> 3, c = lane & 7;
    {
        const int rr = warp * 8 + (lane & 1) * 4 + ((lane >> 1) & 3);
        const int rq = (lane >> 3) * 64 + rr, rf = (lane >> 3) * 40 + rr;
        unsigned short xq = 0, xf = 0;
        const unsigned short* xp = reinterpret_cast<const unsigned short*>(p.x);
        if (lane < 24 && rq < kXR) xq = __ldg(xp + s * kXR + rq);
        if (lane < 16 && warp < 5) xf = __ldg(xp + (cta & 7) * kFR + rf);
        if (tid < kDh) {
            word_st(&g_mail[cta * kDh + tid], 0.f, 0u);
            if (tid / kOC != s) word_st(&g_mail[(2 * kCTAs + cta) * kDh + tid], 0.f, 0u);
        }
        if (lane < 24) sm.sc[warp][kScQ + lane] = bf_lo(xq);
        if (lane < 16) sm.sc[warp][kScF + lane] = bf_lo(xf);
    }
    bar_sync(2, kThreads);
    const unsigned tag = sm.tag;
    const uint32_t lane_off = (uint32_t)((warp * 8 + g) * kRowB + c * 16);
    if (tid == 0) TSTAMP(2);

#pragma unroll 1
    for (int pass = 0; pass < 3; pass++) {
        {
            const int t0 = pass == 0 ? kTQ : (pass == 1 ? kTF : kTV);
            const int t1 = pass == 0 ? kTK : (pass == 1 ? kTV : kTD);
            const float* cf = &sm.sc[warp][(pass == 0 ? kScQ : (pass == 1 ? kScF : 0)) + g * 2];
            float acc[24];
#pragma unroll
            for (int e = 0; e < 24; e++) acc[e] = 0.f;
#pragma unroll 1
            for (int t = t0; t < t1; t++) {
                const uint32_t st = t % kStages;
                const float2 pr = *reinterpret_cast<const float2*>(cf);
                cf += 8;
                const bool on = warp * 8 * kRowB < tile_bytes(t);
                mbar_wait(full0 + 8 * st, (t / kStages) & 1);
                if (on) {
                    const uint32_t a = ring0 + st * kTileB + lane_off;
                    uint4 v[6];
#pragma unroll
                    for (int j = 0; j < 3; j++) { v[j] = lds128(a + j * 128); v[3 + j] = lds128(a + 4 * kRowB + j * 128); }
#pragma unroll
                    for (int j = 0; j < 3; j++) { axpy8(acc + 8 * j, pr.x, v[j]); axpy8(acc + 8 * j, pr.y, v[3 + j]); }
                }
                __syncwarp();
                if (lane == 0) mbar_arrive(empty0 + 8 * st);
            }
            if (tid == 0) TSTAMP(3 + pass);
            float r12[12];
#pragma unroll
            for (int e = 0; e < 12; e++) {
                const float keep = (g & 2) ? acc[12 + e] : acc[e];
                const float send = (g & 2) ? acc[e] : acc[12 + e];
                r12[e] = keep + __shfl_xor_sync(0xffffffffu, send, 16);
            }
#pragma unroll
            for (int e = 0; e < 6; e++) {
                const float keep = (g & 1) ? r12[6 + e] : r12[e];
                const float send = (g & 1) ? r12[e] : r12[6 + e];
                const float r = keep + __shfl_xor_sync(0xffffffffu, send, 8);
                const int ai = g * 6 + e;
                sm.red[warp * kDh + (ai >> 3) * 64 + c * 8 + (ai & 7)] = r;
            }
        }
        bar_sync(pass == 2 ? 4 : 1, pass == 2 ? 288 : 256);
        if (tid < kDh) {
            float o = 0.f;
#pragma unroll
            for (int w = 0; w < kCW; w++) o += sm.red[w * kDh + tid];
            if (pass == 2) o *= sm.oscale;
            if (pass == 2 && tid / kOC == s) sm.q[tid] = o;
            else word_st(&g_mail[(pass * kCTAs + cta) * kDh + tid], o, tag);
        }
        if (pass == 1) bar_sync(3, 288);
        if (pass != 0) continue;

        if (tid < kDh) {
            const unsigned* src = &g_mail[(h * kSplit) * kDh + tid];
            const unsigned* const ps[4] = {src, src + kDh, src + 2 * kDh, src + 3 * kDh};
            float v[4];
            word_wait<4, 1>(ps, tag, v);
            sm.q[tid] = bfr((v[0] + v[1]) + (v[2] + v[3]));
        }
        cbar();
        if (tid == 0) TSTAMP(6);

        {
            float q[24];
#pragma unroll
            for (int j = 0; j < 3; j++) {
                const float4 a = *reinterpret_cast<const float4*>(&sm.q[j * 64 + c * 8]);
                const float4 b = *reinterpret_cast<const float4*>(&sm.q[j * 64 + c * 8 + 4]);
                q[j * 8 + 0] = a.x; q[j * 8 + 1] = a.y; q[j * 8 + 2] = a.z; q[j * 8 + 3] = a.w;
                q[j * 8 + 4] = b.x; q[j * 8 + 5] = b.y; q[j * 8 + 6] = b.z; q[j * 8 + 7] = b.w;
            }
            const float scale = 0.07216878364870322f;
#pragma unroll 1
            for (int t = kTK; t < kTF; t++) {
                const uint32_t st = t % kStages;
                mbar_wait(full0 + 8 * st, (t / kStages) & 1);
                const uint32_t a = ring0 + st * kTileB + lane_off;
                uint4 v[6];
#pragma unroll
                for (int j = 0; j < 3; j++) { v[j] = lds128(a + j * 128); v[3 + j] = lds128(a + 4 * kRowB + j * 128); }
                const float s0 = dot8(q, v[0]) + dot8(q + 8, v[1]) + dot8(q + 16, v[2]);
                const float s1 = dot8(q, v[3]) + dot8(q + 8, v[4]) + dot8(q + 16, v[5]);
                __syncwarp();
                if (lane == 0) mbar_arrive(empty0 + 8 * st);
                float mine = (c & 4) ? s1 : s0;
                const float other = (c & 4) ? s0 : s1;
                mine += __shfl_xor_sync(0xffffffffu, other, 4);
                mine += __shfl_xor_sync(0xffffffffu, mine, 2);
                mine += __shfl_xor_sync(0xffffffffu, mine, 1);
                if ((c & 3) == 0) sm.sc[warp][((t - kTK) * 4 + g) * 2 + (c >> 2)] = bfr(bfr(mine) * scale);
            }
        }
        if (tid == 0) TSTAMP(7);
        {
            __syncwarp();
            float4 sv = *reinterpret_cast<const float4*>(&sm.sc[warp][lane * 4]);
            float m = fmaxf(fmaxf(sv.x, sv.y), fmaxf(sv.z, sv.w));
#pragma unroll
            for (int o = 16; o > 0; o >>= 1) m = fmaxf(m, __shfl_xor_sync(0xffffffffu, m, o));
            if (lane == 0) sm.wmax[warp] = m;
            cbar();
            m = sm.wmax[0];
#pragma unroll
            for (int w = 1; w < kCW; w++) m = fmaxf(m, sm.wmax[w]);
            sv.x = __expf(sv.x - m); sv.y = __expf(sv.y - m); sv.z = __expf(sv.z - m); sv.w = __expf(sv.w - m);
            *reinterpret_cast<float4*>(&sm.sc[warp][lane * 4]) = sv;
            float l = (sv.x + sv.y) + (sv.z + sv.w);
#pragma unroll
            for (int o = 16; o > 0; o >>= 1) l += __shfl_xor_sync(0xffffffffu, l, o);
            if (lane == 0) sm.wsum[warp] = l;
            __syncwarp();
        }
    }
    bar_arrive(5, 288);
    if (tid == 0) TSTAMP(12);

    {
        const int tt = tid < 240 ? tid : 239;
        const int rg3 = tt / 80, ch3 = tt % 80;
        const float4* cf = reinterpret_cast<const float4*>(&sm.coef[rg3][0]);
        float oacc[8];
#pragma unroll
        for (int e = 0; e < 8; e++) oacc[e] = 0.f;
        {
            const float4 c4 = cf[4];
            mbar_wait(full0 + 8 * (kTD % kStages), (kTD / kStages) & 1);
            const uint32_t a = ring0 + (kTD % kStages) * kTileB + rg3 * 4 * kOutRowB + ch3 * 16;
            axpy8(oacc, c4.x, lds128(a)); axpy8(oacc, c4.y, lds128(a + kOutRowB));
            axpy8(oacc, c4.z, lds128(a + 2 * kOutRowB)); axpy8(oacc, c4.w, lds128(a + 3 * kOutRowB));
        }
        float wf[12][8];
#pragma unroll
        for (int j = 0; j < 2; j++) {
            const int t = kTO + j;
            mbar_wait(full0 + 8 * (t % kStages), (t / kStages) & 1);
            const uint32_t a = ring0 + (t % kStages) * kTileB + rg3 * 6 * kOutRowB + ch3 * 16;
#pragma unroll
            for (int i = 0; i < 6; i++) {
                const uint4 v = lds128(a + i * kOutRowB);
                float* w = wf[j * 6 + i];
                w[0] = bf_lo(v.x); w[1] = bf_hi(v.x); w[2] = bf_lo(v.y); w[3] = bf_hi(v.y);
                w[4] = bf_lo(v.z); w[5] = bf_hi(v.z); w[6] = bf_lo(v.w); w[7] = bf_hi(v.w);
#pragma unroll
                for (int e = 0; e < 8; e++) asm volatile("" : "+f"(w[e]));
            }
        }
        if (tid == 0) TSTAMP(13);
        bar_sync(6, 288);
        {
            const float4 c0 = cf[0], c1 = cf[1], c2 = cf[2], c3 = cf[3];
            const float cc[12] = {c0.x, c0.y, c0.z, c0.w, c1.x, c1.y, c1.z, c1.w, c2.x, c2.y, c2.z, c2.w};
#pragma unroll
            for (int i = 0; i < 12; i++)
#pragma unroll
                for (int e = 0; e < 8; e++) oacc[e] = fmaf(cc[i], wf[i][e], oacc[e]);
            const int t = kTO + 2;
            mbar_wait(full0 + 8 * (t % kStages), (t / kStages) & 1);
            const uint32_t a = ring0 + (t % kStages) * kTileB + rg3 * 4 * kOutRowB + ch3 * 16;
            axpy8(oacc, c3.x, lds128(a)); axpy8(oacc, c3.y, lds128(a + kOutRowB));
            axpy8(oacc, c3.z, lds128(a + 2 * kOutRowB)); axpy8(oacc, c3.w, lds128(a + 3 * kOutRowB));
        }
        if (tid == 0) TSTAMP(9);
        if (tid < 240) {
            float4* d = reinterpret_cast<float4*>(&sm.ored[rg3 * kD + ch3 * 8]);
            d[0] = make_float4(oacc[0], oacc[1], oacc[2], oacc[3]);
            d[1] = make_float4(oacc[4], oacc[5], oacc[6], oacc[7]);
        }
    }
    cbar();
    if (tid < kSlots) {
        const float* q = &sm.ored[tid * 3];
        const bool full3 = tid * 3 + 2 < kD;
        const float v0 = q[0] + q[kD] + q[2 * kD];
        const float v1 = full3 ? q[1] + q[kD + 1] + q[2 * kD + 1] : 0.f;
        const float v2 = full3 ? q[2] + q[kD + 2] + q[2 * kD + 2] : 0.f;
        float4* slot = &g_acc[(tid >> 1) * kAccStride + (tid & 1)];
        if (tid == 0) TSTAMP(10);
        const float4 old = atom_add4(slot, v0, v1, v2, 1.0f);
        if (old.w == (float)(kCTAs - 1)) {
            p.out[tid * 3] = __float2bfloat16_rn(old.x + v0);
            if (full3) {
                p.out[tid * 3 + 1] = __float2bfloat16_rn(old.y + v1);
                p.out[tid * 3 + 2] = __float2bfloat16_rn(old.z + v2);
            }
            *slot = make_float4(0.f, 0.f, 0.f, 0.f);
            if (tid == 0) g_epoch = tag;
        }
    }
}

typedef CUresult (*EncodeFn)(CUtensorMap*, CUtensorMapDataType, cuuint32_t, void*, const cuuint64_t*, const cuuint64_t*,
                             const cuuint32_t*, const cuuint32_t*, CUtensorMapInterleave, CUtensorMapSwizzle,
                             CUtensorMapL2promotion, CUtensorMapFloatOOBfill);

void make_map(EncodeFn fn, CUtensorMap* m, void* base, int cols, int box_rows) {
    const cuuint64_t dims[2] = {(cuuint64_t)cols, (cuuint64_t)kD};
    const cuuint64_t strides[1] = {(cuuint64_t)cols * 2};
    const cuuint32_t box[2] = {(cuuint32_t)kDh, (cuuint32_t)box_rows};
    const cuuint32_t estr[2] = {1, 1};
    fn(m, CU_TENSOR_MAP_DATA_TYPE_BFLOAT16, 2, base, dims, strides, box, estr, CU_TENSOR_MAP_INTERLEAVE_NONE,
       CU_TENSOR_MAP_SWIZZLE_NONE, CU_TENSOR_MAP_L2_PROMOTION_NONE, CU_TENSOR_MAP_FLOAT_OOB_FILL_NONE);
}

}

extern "C" void kernel_launch(void* const* d_in, const int* in_sizes, int n_in, void* d_out, int out_size) {
    (void)in_sizes; (void)n_in; (void)out_size;
    static EncodeFn encode = nullptr;
    if (!encode) {
        void* fn = nullptr;
        cudaDriverEntryPointQueryResult qr;
        cudaGetDriverEntryPoint("cuTensorMapEncodeTiled", &fn, cudaEnableDefault, &qr);
        encode = (EncodeFn)fn;
        cudaFuncSetAttribute(fused_decode_kernel, cudaFuncAttributeMaxDynamicSharedMemorySize, (int)sizeof(Smem));
    }
    Params p;
    make_map(encode, &p.tq, d_in[3], kH * kDh, 32);
    make_map(encode, &p.tg, d_in[6], kF, 40);
    make_map(encode, &p.tu, d_in[7], kF, 40);
    p.x = (const __nv_bfloat16*)d_in[0];
    p.k = (const unsigned char*)d_in[1];
    p.v = (const unsigned char*)d_in[2];
    p.wo = (const unsigned char*)d_in[4];
    p.wd = (const unsigned char*)d_in[8];
    p.gate_w = (const __nv_bfloat16*)d_in[9];
    p.out = (__nv_bfloat16*)d_out;
    fused_decode_kernel<<<kCTAs, kThreads, sizeof(Smem), cudaStreamPerThread>>>(p);
}
```

```cpp
#include <cuda_runtime.h>
#include <cuda_bf16.h>
#include <cuda.h>
#include <stdint.h>

namespace {

constexpr int kD = 640;
constexpr int kH = 32;
constexpr int kDh = 192;
constexpr int kSk = 32768;
constexpr int kW = 4096;
constexpr int kF = 1536;
constexpr int kSplit = 4;
constexpr int kCTAs = kH * kSplit;
constexpr int kCW = 8;
constexpr int kThreads = kCW * 32 + 64;
constexpr int kTileKeys = 64;
constexpr int kRowB = kDh * 2;
constexpr int kTileB = kTileKeys * kRowB;
constexpr int kStages = 8;
constexpr int kKVTiles = kW / kSplit / kTileKeys;
constexpr int kOutRowB = kD * 2;
constexpr int kFC = 2 * kF / kCTAs;
constexpr int kOC = 2 * kDh / kSplit;
constexpr int kXR = kD / kSplit;
constexpr int kFR = kD / 8;
constexpr int kTQ = 0;
constexpr int kTK = 3;
constexpr int kTF = kTK + kKVTiles;
constexpr int kTV = kTF + 2;
constexpr int kTD = kTV + kKVTiles;
constexpr int kTO = kTD + 1;
constexpr int kNumTiles = kTO + 3;
constexpr int kSlots = 240;
constexpr unsigned kSpinLimit = 1u << 24;
#define NINIT 3
constexpr int kInit = NINIT;
#define WINDOW 71000
#define PREWRITE 0
#define HELPER_SLEEP 4000
#define ACCSTRIDE 16
#define WINDOW_HI 96000
#define MIDSTART 99
#define MIDEND 34
#define MID_LO 77824
#define MID_HI 125000
#define EXP_PURE 0
#define POLLMODE 1
#define BALSTART 8
#define QPOLL 0
#define ACCGROUP 4
#define SPINLAST 1
#define OBACK 0
#define TAILORD 1
#define QSENT 1
#define L3START 8
#define L3END 99
#define BIAS2 128
#define BIAS0 16
#define TAILSTART 99
#define WINDOW_END 53248
#define BALANCE 2
#define BALANCE_BIAS 72
constexpr uint32_t kWindow = WINDOW;
constexpr uint32_t kWindowHi = WINDOW_HI;
constexpr int kAccStride = ACCSTRIDE;

constexpr int kCbQ = 1024, kCbF = kCbQ + kXR, kCbLen = kCbF + kFR;

struct Smem {
    alignas(1024) unsigned char ring[kStages][kTileB];
    alignas(16) float sc[kCW][128];
    alignas(16) __nv_bfloat16 rowc[kCbLen];
    alignas(16) float q[kDh];
    alignas(16) __nv_bfloat16 coef[128];
    float gate[2];
    float wmax[kCW];
    float wsum[kCW];
    float oscale;
    unsigned tag;
    alignas(8) unsigned long long full[kStages];
    alignas(8) unsigned long long empty[kStages];
    alignas(8) unsigned long long coef_ready;
};

struct Scratch {
    alignas(256) unsigned epoch;
    alignas(256) unsigned accflag;
    alignas(256) unsigned prog;
    alignas(256) unsigned stat[kCTAs * 8];
    alignas(256) unsigned mail[2 * kCTAs * kDh];
    alignas(256) float4 acc[(kSlots + 2) * kAccStride];
};
__device__ Scratch g_scratch;

#define TSTAMP(i) do {} while (0)

__device__ __forceinline__ uint32_t s2u(const void* p) { return (uint32_t)__cvta_generic_to_shared(p); }

__device__ __forceinline__ void mbar_init(uint32_t bar, uint32_t cnt) {
    asm volatile("mbarrier.init.shared::cta.b64 [%0], %1;" ::"r"(bar), "r"(cnt) : "memory");
}
__device__ __forceinline__ void mbar_expect_tx(uint32_t bar, uint32_t bytes) {
    asm volatile("mbarrier.arrive.expect_tx.shared::cta.b64 _, [%0], %1;" ::"r"(bar), "r"(bytes) : "memory");
}
__device__ __forceinline__ void mbar_arrive(uint32_t bar) {
    asm volatile("mbarrier.arrive.shared::cta.b64 _, [%0];" ::"r"(bar) : "memory");
}
__device__ __forceinline__ void mbar_wait(uint32_t bar, uint32_t parity) {
    asm volatile("{\n.reg .pred p;\n.reg .u32 n;\nmov.u32 n, 0;\n"
                 "WL:\nmbarrier.try_wait.parity.shared::cta.b64 p, [%0], %1;\n@p bra WD;\n"
                 "add.u32 n, n, 1;\nsetp.lt.u32 p, n, %2;\n@p bra WL;\ntrap;\nWD:\n}"
                 ::"r"(bar), "r"(parity), "n"(kSpinLimit) : "memory");
}
__device__ __forceinline__ bool mbar_test(uint32_t bar, uint32_t parity) {
    uint32_t ok;
    asm volatile("{\n.reg .pred p;\nmbarrier.test_wait.parity.shared::cta.b64 p, [%1], %2;\nselp.u32 %0, 1, 0, p;\n}"
                 : "=r"(ok) : "r"(bar), "r"(parity) : "memory");
    return ok != 0;
}
__device__ __forceinline__ void mbar_spin(uint32_t bar, uint32_t parity) {
    asm volatile("{\n.reg .pred p;\n.reg .u32 n;\nmov.u32 n, 0;\n"
                 "WL:\nmbarrier.test_wait.parity.shared::cta.b64 p, [%0], %1;\n@p bra WD;\n"
                 "add.u32 n, n, 1;\nsetp.lt.u32 p, n, %2;\n@p bra WL;\ntrap;\nWD:\n}"
                 ::"r"(bar), "r"(parity), "n"(kSpinLimit) : "memory");
}
#define EVICT_FIRST 1
__device__ __forceinline__ void bulk_g2s(uint32_t dst, const void* src, uint32_t bytes, uint32_t bar, uint64_t pol) {
    asm volatile("cp.async.bulk.shared::cluster.global.mbarrier::complete_tx::bytes.L2::cache_hint [%0], [%1], %2, [%3], %4;"
                 ::"r"(dst), "l"(src), "r"(bytes), "r"(bar), "l"(pol) : "memory");
}
__device__ __forceinline__ void tma_3d(uint32_t dst, const CUtensorMap* map, int c1, int c2, uint32_t bar, uint64_t pol) {
    asm volatile("cp.async.bulk.tensor.3d.shared::cluster.global.mbarrier::complete_tx::bytes.L2::cache_hint [%0], [%1, {%4, %3, %6}], [%2], %5;"
                 ::"r"(dst), "l"(map), "r"(bar), "r"(c1), "r"(0), "l"(pol), "r"(c2) : "memory");
}
__device__ __forceinline__ void ldsm4t(uint32_t (&r)[4], uint32_t a) {
    asm volatile("ldmatrix.sync.aligned.m8n8.x4.trans.shared.b16 {%0,%1,%2,%3}, [%4];"
                 : "=r"(r[0]), "=r"(r[1]), "=r"(r[2]), "=r"(r[3]) : "r"(a));
}
__device__ __forceinline__ void mma16816(float (&d)[4], const uint32_t (&a)[4], uint32_t b0, uint32_t b1) {
    asm volatile("mma.sync.aligned.m16n8k16.row.col.f32.bf16.bf16.f32 {%0,%1,%2,%3}, {%4,%5,%6,%7}, {%8,%9}, {%0,%1,%2,%3};"
                 : "+f"(d[0]), "+f"(d[1]), "+f"(d[2]), "+f"(d[3]) : "r"(a[0]), "r"(a[1]), "r"(a[2]), "r"(a[3]), "r"(b0), "r"(b1));
}
__device__ __forceinline__ uint4 ldg128(const void* p) {
    uint4 v;
    asm volatile("ld.global.nc.v4.u32 {%0,%1,%2,%3}, [%4];" : "=r"(v.x), "=r"(v.y), "=r"(v.z), "=r"(v.w) : "l"(p));
    return v;
}
__device__ __forceinline__ uint4 lds128(uint32_t a) {
    uint4 v;
    asm volatile("ld.shared.v4.u32 {%0,%1,%2,%3}, [%4];" : "=r"(v.x), "=r"(v.y), "=r"(v.z), "=r"(v.w) : "r"(a));
    return v;
}
__device__ __forceinline__ void word_st(unsigned* p, float v, unsigned tag) {
    asm volatile("st.relaxed.gpu.global.u32 [%0], %1;" ::"l"(p), "r"((__float_as_uint(v) & ~3u) | tag) : "memory");
}
template <int N, int W, int MODE = 0, int BACKOFF = 0>
__device__ __forceinline__ void word_wait(const unsigned* const (&p)[N], unsigned tag, float (&v)[N * W]) {
    unsigned n = 0;
#pragma unroll 1
    while (true) {
        unsigned r[N * W];
#pragma unroll
        for (int j = 0; j < N; j++) {
            if (W == 1 && MODE == 1) asm volatile("atom.relaxed.gpu.global.or.b32 %0, [%1], 0;" : "=r"(r[j]) : "l"(p[j]) : "memory");
            else if (W == 1) asm volatile("ld.relaxed.gpu.global.u32 %0, [%1];" : "=r"(r[j]) : "l"(p[j]) : "memory");
            else if (MODE == 1) asm volatile("{\n.reg .b64 w;\natom.relaxed.gpu.global.or.b64 w, [%2], 0;\nmov.b64 {%0,%1}, w;\n}" : "=r"(r[j * W]), "=r"(r[j * W + W - 1]) : "l"(p[j]) : "memory");
            else if (MODE == 2) asm volatile("ld.relaxed.sys.global.v2.u32 {%0,%1}, [%2];" : "=r"(r[j * W]), "=r"(r[j * W + W - 1]) : "l"(p[j]) : "memory");
            else if (MODE == 3) asm volatile("ld.volatile.global.v2.u32 {%0,%1}, [%2];" : "=r"(r[j * W]), "=r"(r[j * W + W - 1]) : "l"(p[j]) : "memory");
            else asm volatile("ld.relaxed.gpu.global.v2.u32 {%0,%1}, [%2];" : "=r"(r[j * W]), "=r"(r[j * W + W - 1]) : "l"(p[j]) : "memory");
        }
        unsigned bad = 0;
#pragma unroll
        for (int j = 0; j < N * W; j++) { bad |= (r[j] ^ tag) & 3u; v[j] = __uint_as_float(r[j] & ~3u); }
        if (bad == 0) break;
        if (++n > kSpinLimit) __trap();
        if (BACKOFF > 1) __nanosleep(BACKOFF);
    }
}
__device__ __forceinline__ float4 atom_add4(float4* p, float a, float b, float c, float d) {
    float4 r;
    asm volatile("atom.relaxed.gpu.global.add.v4.f32 {%0,%1,%2,%3}, [%4], {%5,%6,%7,%8};"
                 : "=f"(r.x), "=f"(r.y), "=f"(r.z), "=f"(r.w) : "l"(p), "f"(a), "f"(b), "f"(c), "f"(d) : "memory");
    return r;
}
__device__ __forceinline__ float4* acc_slot(Scratch* g, int i) { return &g->acc[(i / ACCGROUP) * kAccStride + (i % ACCGROUP)]; }
__device__ __forceinline__ void cbar() { asm volatile("bar.sync 1, 256;" ::: "memory"); }
__device__ __forceinline__ void bar_sync(int id, int n) { asm volatile("bar.sync %0, %1;" ::"r"(id), "r"(n) : "memory"); }
__device__ __forceinline__ void bar_arrive(int id, int n) { asm volatile("bar.arrive %0, %1;" ::"r"(id), "r"(n) : "memory"); }

__device__ __forceinline__ void st_bf16(__nv_bfloat16* p, float v) {
    asm volatile("st.global.u16 [%0], %1;" ::"l"(p), "h"(__bfloat16_as_ushort(__float2bfloat16_rn(v))) : "memory");
}
__device__ __forceinline__ float fsel(bool c, float a, float b) {
    float r;
    asm("{\n.reg .pred p;\nsetp.ne.u32 p, %3, 0;\nselp.f32 %0, %1, %2, p;\n}" : "=f"(r) : "f"(a), "f"(b), "r"((unsigned)c));
    return r;
}
__device__ __forceinline__ float bf_lo(uint32_t w) { return __uint_as_float(w << 16); }
__device__ __forceinline__ float bf_hi(uint32_t w) { return __uint_as_float(w & 0xffff0000u); }
__device__ __forceinline__ float bfr(float v) { return __bfloat162float(__float2bfloat16_rn(v)); }

__device__ __forceinline__ void axpy8(float* acc, float c, const uint4& v) {
    acc[0] = fmaf(c, bf_lo(v.x), acc[0]); acc[1] = fmaf(c, bf_hi(v.x), acc[1]);
    acc[2] = fmaf(c, bf_lo(v.y), acc[2]); acc[3] = fmaf(c, bf_hi(v.y), acc[3]);
    acc[4] = fmaf(c, bf_lo(v.z), acc[4]); acc[5] = fmaf(c, bf_hi(v.z), acc[5]);
    acc[6] = fmaf(c, bf_lo(v.w), acc[6]); acc[7] = fmaf(c, bf_hi(v.w), acc[7]);
}
__device__ __forceinline__ float dot8(const float* q, const uint4& v) {
    float a = q[0] * bf_lo(v.x), b = q[1] * bf_hi(v.x);
    a = fmaf(q[2], bf_lo(v.y), a); b = fmaf(q[3], bf_hi(v.y), b);
    a = fmaf(q[4], bf_lo(v.z), a); b = fmaf(q[5], bf_hi(v.z), b);
    a = fmaf(q[6], bf_lo(v.w), a); b = fmaf(q[7], bf_hi(v.w), b);
    return a + b;
}

__host__ __device__ constexpr uint32_t tile_bytes(int t) {
    return (t == kTQ + 2 || t == kTF + 1) ? 32 * kRowB
         : t == kTF ? 48 * kRowB
         : t == kTD ? 12 * kOutRowB
         : t >= kTO ? 16 * kOutRowB : kTileB;
}
constexpr int must_land(int t, uint32_t win) {
    uint32_t sum = 0;
    for (int j = t; j >= 0; j--) { sum += tile_bytes(j); if (sum > win) return j; }
    return -1;
}
constexpr uint32_t win_lo(int t) { return t >= TAILSTART ? WINDOW_END : (t >= MIDSTART && t < MIDEND) ? MID_LO : kWindow; }
constexpr uint32_t win_hi(int t) { return t >= TAILSTART ? WINDOW_END : (t >= MIDSTART && t < MIDEND) ? MID_HI : kWindowHi; }
constexpr uint64_t pack_back(int first, bool hi) {
    uint64_t r = 0;
    for (int t = first; t < first + 21 && t < kNumTiles; t++) {
        const int d = t - must_land(t, hi ? win_hi(t) : win_lo(t));
        r |= (uint64_t)(d > 7 ? 7 : d) << (3 * (t - first));
    }
    return r;
}
constexpr uint64_t kBackLoA = pack_back(0, false), kBackLoB = pack_back(21, false);
constexpr uint64_t kBackHiA = pack_back(0, true), kBackHiB = pack_back(21, true);
template <bool HI>
__device__ __forceinline__ int look_back(int t) {
    const uint64_t a = HI ? kBackHiA : kBackLoA, b = HI ? kBackHiB : kBackLoB;
    return (int)(((t < 21 ? a : b) >> (3 * (t < 21 ? t : t - 21))) & 7);
}

__device__ __forceinline__ bool elect_one() {
    uint32_t ok;
    asm volatile("{\n.reg .pred p;\nelect.sync _|p, 0xffffffff;\nselp.u32 %0, 1, 0, p;\n}" : "=r"(ok));
    return ok != 0;
}

struct Params {
    const __nv_bfloat16* x;
    const unsigned char* k;
    const __nv_bfloat16* gate_w;
    __nv_bfloat16* out;
    Scratch* g;
    CUtensorMap tq;
    CUtensorMap tg;
    CUtensorMap tu;
    CUtensorMap tv;
    CUtensorMap td;
    CUtensorMap to;
};

__global__ void __launch_bounds__(kThreads, 1) fused_decode_kernel(const __grid_constant__ Params p) {
    extern __shared__ __align__(1024) unsigned char smem_raw[];
    Smem& sm = *reinterpret_cast<Smem*>(smem_raw);
    const int tid = threadIdx.x;
    const int lane = tid & 31;
    const int warp = tid >> 5;
    const int cta = blockIdx.x;
    const int h = cta >> 2;
    const int s = cta & 3;
    const uint32_t ring0 = s2u(&sm.ring[0][0]);
    const uint32_t full0 = s2u(&sm.full[0]);
    const uint32_t empty0 = s2u(&sm.empty[0]);

    uint64_t pol;
    asm volatile("createpolicy.fractional.L2::evict_first.b64 %0, 1.0;" : "=l"(pol));
    if (warp == kCW && elect_one()) {
        TSTAMP(0);
#pragma unroll
        for (int i = 0; i < kInit; i++) mbar_init(full0 + 8 * i, 1);
        asm volatile("fence.mbarrier_init.release.cluster;" ::: "memory");
#pragma unroll
        for (int i = 0; i < kInit; i++) {
            mbar_expect_tx(full0 + 8 * i, tile_bytes(i));
            tma_3d(ring0 + i * kTileB, &p.tq, h * 3, s * kXR + i * 64, full0 + 8 * i, pol);
            if (i < 2) tma_3d(ring0 + i * kTileB + 32 * kRowB, &p.tq, h * 3, s * kXR + i * 64 + 32, full0 + 8 * i, pol);
        }
        TSTAMP(1);
    }
    __syncwarp();

    if (warp == kCW) {
        const bool leader = elect_one();
        bar_sync(6, 64);
        bar_arrive(2, kThreads);
        const int key0 = h * kSk + (kSk - kW) + s * kTileKeys;
        const unsigned char* src = p.k + (size_t)key0 * kRowB;
        unsigned prog = 0;
#pragma unroll 1
        for (int t = kInit; t < kNumTiles; t++) {
            const uint32_t bytes = tile_bytes(t);
            const uint32_t st = t % kStages;
            if (t >= kStages) mbar_wait(empty0 + 8 * st, ((t / kStages) - 1) & 1);
            if (leader) mbar_expect_tx(full0 + 8 * st, bytes);
            int need = t - look_back<false>(t);
            if (t >= BALSTART) {
                const int lead = (t - kInit) * kCTAs - (int)__shfl_sync(0xffffffffu, prog, 0);
                need += (lead > BIAS2) - (lead <= BALANCE_BIAS) - (lead <= BIAS0);
            }
            if (need >= 0) mbar_wait(full0 + 8 * (need % kStages), (need / kStages) & 1);
            if (t == kTF || t == kTF + 1) {
                if (leader) {
                    const CUtensorMap* m = cta < 64 ? &p.tg : &p.tu;
                    const int row = (cta & 7) * kFR + (t - kTF) * 48, blk = ((cta >> 3) & 7) * 3;
                    tma_3d(ring0 + st * kTileB, m, blk, row, full0 + 8 * st, pol);
                    tma_3d(ring0 + st * kTileB + 16 * kRowB, m, blk, row + 16, full0 + 8 * st, pol);
                    if (t == kTF) tma_3d(ring0 + st * kTileB + 32 * kRowB, m, blk, row + 32, full0 + 8 * st, pol);
                }
            } else if (t >= kTV && t < kTD) {
                if (leader) tma_3d(ring0 + st * kTileB, &p.tv, 0, key0 + (t - kTV) * (kSplit * kTileKeys), full0 + 8 * st, pol);
            } else if (t >= kTD) {
                if (leader) tma_3d(ring0 + st * kTileB, t == kTD ? &p.td : &p.to, t == kTD ? (cta >> 1) * kFC : (cta >> 1) * kOC + (t - kTO) * 32,
                                   (cta & 1) * 5, full0 + 8 * st, pol);
            } else {
                if (leader) bulk_g2s(ring0 + st * kTileB, src, kTileB, full0 + 8 * st, pol);
                src += kSplit * kTileB;
            }
            if (leader) TSTAMP(16 + t);
            if (lane == 0) {
                if (t + 1 >= BALSTART)
                    asm volatile("atom.relaxed.gpu.global.inc.u32 %0, [%1], %2;" : "=r"(prog) : "l"(&p.g->prog), "n"((kNumTiles - kInit) * kCTAs - 1) : "memory");
                else
                    asm volatile("red.relaxed.gpu.global.inc.u32 [%0], %1;" ::"l"(&p.g->prog), "n"((kNumTiles - kInit) * kCTAs - 1) : "memory");
            }
        }
        if (lane == 0 && prog == (kNumTiles - kInit) * kCTAs - 1) p.g->epoch = sm.tag % 3u + 1u;
        return;
    }

    if (warp == kCW + 1) {
        if (elect_one()) {
#pragma unroll
            for (int i = 0; i < kStages; i++) { if (i >= kInit) mbar_init(full0 + 8 * i, 1); mbar_init(empty0 + 8 * i, kCW); }
            mbar_init(s2u(&sm.coef_ready), 1);
            asm volatile("fence.mbarrier_init.release.cluster;" ::: "memory");
        }
        __syncwarp();
        bar_arrive(6, 64);
    }
    if (warp == kCW + 1) {
        unsigned e = 0;
        if (lane == 31) asm volatile("ld.relaxed.gpu.global.u32 %0, [%1];" : "=r"(e) : "l"(&p.g->epoch) : "memory");
        if (lane < 30) {
            const uint4 v = ldg128(p.x + (lane < 20 ? s * kXR + lane * 8 : (cta & 7) * kFR + (lane - 20) * 8));
            *reinterpret_cast<uint4*>(&sm.rowc[kCbQ + lane * 8]) = v;
        }
        const unsigned tag = __shfl_sync(0xffffffffu, e, 31) % 3u + 1u;
        if (lane == 0) sm.tag = tag;
        bar_arrive(2, kThreads);
        __nanosleep(3000);
        if (cta == 0) {
            for (int i = lane; i < kSlots; i += 32) *acc_slot(p.g, i) = make_float4(0.f, 0.f, 0.f, 0.f);
            __threadfence();
            __syncwarp();
            if (lane == 0) asm volatile("st.relaxed.gpu.global.u32 [%0], %1;" ::"l"(&p.g->accflag), "r"(tag) : "memory");
        }
        uint4 gx[3], gw[3];
#pragma unroll
        for (int j = 0; j < 3; j++) {
            gx[j] = gw[j] = make_uint4(0, 0, 0, 0);
            if (lane + 32 * j < kD / 8) {
                gx[j] = ldg128(p.x + (lane + 32 * j) * 8);
                gw[j] = ldg128(p.gate_w + (lane + 32 * j) * 8);
            }
        }
        float z = 0.f;
#pragma unroll
        for (int j = 0; j < 3; j++) {
            z += bfr(bf_lo(gx[j].x) * bf_lo(gw[j].x)) + bfr(bf_hi(gx[j].x) * bf_hi(gw[j].x));
            z += bfr(bf_lo(gx[j].y) * bf_lo(gw[j].y)) + bfr(bf_hi(gx[j].y) * bf_hi(gw[j].y));
            z += bfr(bf_lo(gx[j].z) * bf_lo(gw[j].z)) + bfr(bf_hi(gx[j].z) * bf_hi(gw[j].z));
            z += bfr(bf_lo(gx[j].w) * bf_lo(gw[j].w)) + bfr(bf_hi(gx[j].w) * bf_hi(gw[j].w));
        }
#pragma unroll
        for (int o = 16; o > 0; o >>= 1) z += __shfl_xor_sync(0xffffffffu, z, o);
        const float gate = bfr(1.0f / (1.0f + __expf(-bfr(z))));

        bar_sync(3, 288);
        {
            float m = sm.wmax[lane & 7], l = sm.wsum[lane & 7];
#pragma unroll
            for (int o = 4; o > 0; o >>= 1) {
                m = fmaxf(m, __shfl_xor_sync(0xffffffffu, m, o));
                l += __shfl_xor_sync(0xffffffffu, l, o);
            }
            if (lane < 8) word_st(&p.g->stat[cta * 8 + lane], lane ? l : m, tag);
            __nanosleep(HELPER_SLEEP);
            const unsigned* const ps[1] = {&p.g->stat[(h * kSplit + (lane & 3)) * 8]};
            float v[2];
            word_wait<1, 2>(ps, tag, v);
            float M = fmaxf(v[0], __shfl_xor_sync(0xffffffffu, v[0], 1));
            M = fmaxf(M, __shfl_xor_sync(0xffffffffu, M, 2));
            const float w = __expf(v[0] - M);
            float L = w * v[1];
            L += __shfl_xor_sync(0xffffffffu, L, 1);
            L += __shfl_xor_sync(0xffffffffu, L, 2);
            if (lane == s) sm.oscale = w / L;
        }
        {
            const int mtx = lane >> 4, rb = (lane >> 1) & 7, half = lane & 1;
            const unsigned* src = &p.g->mail[(kCTAs + (mtx * 8 + (cta >> 4)) * 8 + rb) * kDh + ((cta >> 1) & 7) * kFC + half * 12];
            const unsigned* const ps[6] = {src, src + 2, src + 4, src + 6, src + 8, src + 10};
            float v[12];
            word_wait<6, 2>(ps, tag, v);
            if (lane == 0) { sm.gate[0] = gate; sm.gate[1] = bfr(1.0f - gate); }
            if (lane < 8) sm.coef[kOC + kFC + lane] = __float2bfloat16_rn(0.f);
#pragma unroll
            for (int j = 0; j < 12; j++) {
                v[j] += __shfl_xor_sync(0xffffffffu, v[j], 2);
                v[j] += __shfl_xor_sync(0xffffffffu, v[j], 4);
                v[j] += __shfl_xor_sync(0xffffffffu, v[j], 8);
                const float gt = bfr(v[j]);
                const float up = __shfl_xor_sync(0xffffffffu, gt, 16);
                if (lane < 2) sm.coef[kOC + half * 12 + j] = __float2bfloat16_rn((gt > 0.f ? gt : gt * 0.f) * up);
            }
        }
        {
            const unsigned* const ps[1] = {&p.g->accflag};
            float v[1];
            word_wait<1, 1>(ps, tag, v);
            __threadfence();
        }
        bar_arrive(4, 288);
        const int d0 = (s >> 1) * kOC + lane * 4;
        const unsigned* src = &p.g->mail[(h * kSplit) * kDh + d0];
        const unsigned* pa = src + ((s + 1) & 3) * kDh;
        const unsigned* pb = src + ((s + 2) & 3) * kDh;
        const unsigned* pc = src + ((s + 3) & 3) * kDh;
        asm volatile("" : "+l"(pa), "+l"(pb), "+l"(pc));
        bar_sync(5, 288);
        if (lane < 24) {
            const unsigned* const ps[6] = {pa, pa + 2, pb, pb + 2, pc, pc + 2};
            const float4 own = *reinterpret_cast<const float4*>(&sm.q[d0]);
            float v[12];
            word_wait<6, 2, POLLMODE, OBACK>(ps, tag % 3u + 1u, v);
            uint2 r;
            __nv_bfloat162 lo = __floats2bfloat162_rn((own.x + v[4]) + (v[0] + v[8]), (own.y + v[5]) + (v[1] + v[9]));
            __nv_bfloat162 hi = __floats2bfloat162_rn((own.z + v[6]) + (v[2] + v[10]), (own.w + v[7]) + (v[3] + v[11]));
            r.x = *reinterpret_cast<uint32_t*>(&lo); r.y = *reinterpret_cast<uint32_t*>(&hi);
            *reinterpret_cast<uint2*>(&sm.coef[lane * 4]) = r;
        }
        __syncwarp();
        if (lane == 0) { TSTAMP(8); mbar_arrive(s2u(&sm.coef_ready)); }
        return;
    }

    const int g = lane >> 3, c = lane & 7;
    bar_sync(2, kThreads);
    const unsigned tag = sm.tag;
    const uint32_t lane_off = (uint32_t)((warp * 8 + g) * kRowB + c * 16);
    if (tid == 0) TSTAMP(2);
    if ((PREWRITE & 4) && tid < kDh) word_st(&p.g->mail[cta * kDh + tid], 0.f, 0u);

    const int mg = lane >> 2, tq = lane & 3;
    const int lk = (lane & 7) + ((lane >> 4) << 3);
    const int mydim = warp * 32 + tq * 8 + mg;
    uint32_t voff[2];
#pragma unroll
    for (int i = 0; i < 2; i++) {
        const int line = lk * 3 + (warp >> 1);
        voff[i] = line * 128 + (((((warp & 1) * 4 + 2 * i + ((lane >> 3) & 1)) ^ line) & 7) << 4);
    }
#pragma unroll 1
    for (int pass = 0; pass < 3; pass++) {
        {
            const int t0 = pass == 0 ? kTQ : (pass == 1 ? kTF : kTV);
            const int t1 = pass == 0 ? kTK : (pass == 1 ? kTV : kTD);
            const uint32_t* cf = reinterpret_cast<const uint32_t*>(&sm.rowc[pass == 0 ? kCbQ : (pass == 1 ? kCbF : 0)]) + tq;
            float d[4][4];
#pragma unroll
            for (int i = 0; i < 4; i++) d[i][0] = d[i][1] = d[i][2] = d[i][3] = 0.f;
            float scale = 1.f;
#pragma unroll 1
            for (int t = t0; t < t1; t++) {
                const uint32_t st = t % kStages;
                const int nk = tile_bytes(t) / (16 * kRowB);
                if (t == kTD - 2) { bar_sync(4, 288); scale = sm.oscale; }
                uint32_t b[8];
#pragma unroll
                for (int j = 0; j < 8; j++) b[j] = cf[j * 4];
                cf += nk * 8;
                mbar_wait(full0 + 8 * st, (t / kStages) & 1);
                if (warp < 6) {
                    const uint32_t a = ring0 + st * kTileB;
                    uint32_t w[8][4];
#pragma unroll
                    for (int j = 0; j < 4; j++) ldsm4t(w[j], a + voff[j & 1] + (j >> 1) * (16 * kRowB));
                    if (nk > 2) {
                        ldsm4t(w[4], a + voff[0] + 2 * (16 * kRowB));
                        ldsm4t(w[5], a + voff[1] + 2 * (16 * kRowB));
                    }
                    if (nk > 3) {
                        ldsm4t(w[6], a + voff[0] + 3 * (16 * kRowB));
                        ldsm4t(w[7], a + voff[1] + 3 * (16 * kRowB));
                    }
#pragma unroll
                    for (int j = 0; j < 4; j++) mma16816(d[j], w[j], b[(j >> 1) * 2], b[(j >> 1) * 2 + 1]);
                    if (nk > 2) { mma16816(d[0], w[4], b[4], b[5]); mma16816(d[1], w[5], b[4], b[5]); }
                    if (nk > 3) { mma16816(d[2], w[6], b[6], b[7]); mma16816(d[3], w[7], b[6], b[7]); }
                }
                __syncwarp();
                if (lane == 0) mbar_arrive(empty0 + 8 * st);
            }
            if (tid == 0) TSTAMP(3 + pass);
            if (warp < 6) {
                const float lo = fsel(tq & 2, fsel(tq & 1, d[1][2], d[1][0]), fsel(tq & 1, d[0][2], d[0][0]));
                const float hi = fsel(tq & 2, fsel(tq & 1, d[3][2], d[3][0]), fsel(tq & 1, d[2][2], d[2][0]));
                const float o = (lo + hi) * scale;
                word_st(&p.g->mail[((pass & 1) * kCTAs + cta) * kDh + mydim], o, pass == 2 ? tag % 3u + 1u : tag);
                if (pass == 2) sm.q[mydim] = __uint_as_float(__float_as_uint(o) & ~3u);
            }
        }
        if (pass == 1) bar_sync(3, 288);
        if (pass != 0) continue;

        if (tid < kDh) {
            const unsigned* src = &p.g->mail[(h * kSplit) * kDh + tid];
            {
                const unsigned* const p1[1] = {src - lane + (lane & 3) * kDh};
                float v1[1];
                if (lane < 4) word_wait<1, 1, 1, QSENT>(p1, tag, v1);
                __syncwarp();
            }
            const unsigned* const ps[4] = {src, src + kDh, src + 2 * kDh, src + 3 * kDh};
            float v[4];
            word_wait<4, 1, QPOLL>(ps, tag, v);
            sm.q[tid] = bfr((v[0] + v[1]) + (v[2] + v[3]));
        }
        cbar();
        if (tid == 0) TSTAMP(6);

        {
            float q[24];
#pragma unroll
            for (int j = 0; j < 3; j++) {
                const float4 a = *reinterpret_cast<const float4*>(&sm.q[j * 64 + c * 8]);
                const float4 b = *reinterpret_cast<const float4*>(&sm.q[j * 64 + c * 8 + 4]);
                q[j * 8 + 0] = a.x; q[j * 8 + 1] = a.y; q[j * 8 + 2] = a.z; q[j * 8 + 3] = a.w;
                q[j * 8 + 4] = b.x; q[j * 8 + 5] = b.y; q[j * 8 + 6] = b.z; q[j * 8 + 7] = b.w;
            }
            const float scale = 0.07216878364870322f;
#pragma unroll 1
            for (int t = kTK; t < kTF; t++) {
                const uint32_t st = t % kStages;
                mbar_wait(full0 + 8 * st, (t / kStages) & 1);
                const uint32_t a = ring0 + st * kTileB + lane_off;
                uint4 v[6];
#pragma unroll
                for (int j = 0; j < 3; j++) { v[j] = lds128(a + j * 128); v[3 + j] = lds128(a + 4 * kRowB + j * 128); }
                const float s0 = dot8(q, v[0]) + dot8(q + 8, v[1]) + dot8(q + 16, v[2]);
                const float s1 = dot8(q, v[3]) + dot8(q + 8, v[4]) + dot8(q + 16, v[5]);
                __syncwarp();
                if (lane == 0) mbar_arrive(empty0 + 8 * st);
                float mine = (c & 4) ? s1 : s0;
                const float other = (c & 4) ? s0 : s1;
                mine += __shfl_xor_sync(0xffffffffu, other, 4);
                mine += __shfl_xor_sync(0xffffffffu, mine, 2);
                mine += __shfl_xor_sync(0xffffffffu, mine, 1);
                if ((c & 3) == 0) sm.sc[warp][(t - kTK) * 8 + c + g] = bfr(bfr(mine) * scale);
            }
        }
        if (tid == 0) TSTAMP(7);
        {
            __syncwarp();
            float4 sv = *reinterpret_cast<const float4*>(&sm.sc[warp][lane * 4]);
            float m = fmaxf(fmaxf(sv.x, sv.y), fmaxf(sv.z, sv.w));
#pragma unroll
            for (int o = 16; o > 0; o >>= 1) m = fmaxf(m, __shfl_xor_sync(0xffffffffu, m, o));
            if (lane == 0) sm.wmax[warp] = m;
            cbar();
            m = sm.wmax[0];
#pragma unroll
            for (int w = 1; w < kCW; w++) m = fmaxf(m, sm.wmax[w]);
            sv.x = __expf(sv.x - m); sv.y = __expf(sv.y - m); sv.z = __expf(sv.z - m); sv.w = __expf(sv.w - m);
            const __nv_bfloat162 p01 = __floats2bfloat162_rn(sv.x, sv.y), p23 = __floats2bfloat162_rn(sv.z, sv.w);
            *reinterpret_cast<uint2*>(&sm.rowc[(lane >> 1) * kTileKeys + warp * 8 + (lane & 1) * 4]) =
                make_uint2(*reinterpret_cast<const uint32_t*>(&p01), *reinterpret_cast<const uint32_t*>(&p23));
            float l = (sv.x + sv.y) + (sv.z + sv.w);
#pragma unroll
            for (int o = 16; o > 0; o >>= 1) l += __shfl_xor_sync(0xffffffffu, l, o);
            if (lane == 0) sm.wsum[warp] = l;
            __syncwarp();
        }
    }
    bar_arrive(5, 288);
    if (tid == 0) TSTAMP(12);

    if (warp < 5) {
        const uint32_t* cw = reinterpret_cast<const uint32_t*>(sm.coef);
        int tqp = tq;
        asm volatile("" : "+r"(tqp));
        const bool q0 = tqp == 0, q1 = tqp == 1;
        float4* slot = acc_slot(p.g, (((cta & 1) * 5 + warp) * 8 + mg) * 3 + tq);
        __nv_bfloat16* o = p.out + ((cta & 1) * 5 + warp) * 64 + tq * 24 + mg;
        float d[4][4];
        uint32_t off[4], w0[8][4], w1[8][4];
        float f0, f1, f2;
#pragma unroll
        for (int i = 0; i < 4; i++) off[i] = lk * 128 + ((((2 * i + ((lane >> 3) & 1)) ^ lk) & 7) << 4);
        {
            const uint32_t b0 = cw[48 + tq], b1 = cw[52 + tq], b2 = cw[56 + tq], b3 = cw[60 + tq];
            const float gb = sm.gate[1];
            const uint32_t a = ring0 + (kTD % kStages) * kTileB + warp * kFC * 128;
            mbar_wait(full0 + 8 * (kTD % kStages), (kTD / kStages) & 1);
#pragma unroll
            for (int i = 0; i < 4; i++) {
                ldsm4t(w0[i], a + off[i]);
                ldsm4t(w0[4 + i], a + off[i] + (lane < 16 ? 16 : 8) * 128);
            }
#pragma unroll
            for (int i = 0; i < 4; i++) {
                d[i][0] = d[i][1] = d[i][2] = d[i][3] = 0.f;
                mma16816(d[i], w0[i], b0, b1);
                mma16816(d[i], w0[4 + i], b2, b3);
            }
            f0 = gb * fsel(q0, d[0][0], fsel(q1, d[1][2], d[3][0]));
            f1 = gb * fsel(q0, d[0][2], fsel(q1, d[2][0], d[3][2]));
            f2 = gb * fsel(q0, d[1][0], d[2][2]);
        }
#pragma unroll
        for (int i = 0; i < 4; i++) off[i] += ring0 + warp * 32 * 128;
        asm volatile("" : "+r"(off[0]), "+r"(off[1]), "+r"(off[2]), "+r"(off[3]));
        mbar_wait(full0 + 8 * (kTO % kStages), (kTO / kStages) & 1);
#pragma unroll
        for (int i = 0; i < 8; i++) ldsm4t(w0[i], off[i & 3] + (kTO % kStages) * kTileB + (i >> 2) * 2048);
        uint32_t b[12];
        float ga = sm.gate[0];
#pragma unroll
        for (int i = 0; i < 4; i++) d[i][0] = d[i][1] = d[i][2] = d[i][3] = 0.f;
        const bool early = __all_sync(0xffffffffu, mbar_test(s2u(&sm.coef_ready), 0));
        if (early) {
#pragma unroll
            for (int j = 0; j < 12; j++) b[j] = cw[j * 4 + tq];
#pragma unroll
            for (int i = 0; i < 8; i++) mma16816(d[i & 3], w0[i], b[(i >> 2) * 2], b[(i >> 2) * 2 + 1]);
        }
        asm volatile("" : "+l"(slot), "+l"(o), "+f"(ga), "+f"(f0), "+f"(f1), "+f"(f2));
        mbar_wait(full0 + 8 * ((kTO + 1) % kStages), ((kTO + 1) / kStages) & 1);
#pragma unroll
        for (int i = 0; i < 8; i++) ldsm4t(w1[i], off[i & 3] + ((kTO + 1) % kStages) * kTileB + (i >> 2) * 2048);
        if (!early) {
            mbar_wait(s2u(&sm.coef_ready), 0);
#pragma unroll
            for (int j = 0; j < 12; j++) b[j] = cw[j * 4 + tq];
#pragma unroll
            for (int i = 0; i < 8; i++) mma16816(d[i & 3], w0[i], b[(i >> 2) * 2], b[(i >> 2) * 2 + 1]);
        }
#pragma unroll
        for (int i = 0; i < 8; i++) mma16816(d[i & 3], w1[i], b[4 + (i >> 2) * 2], b[5 + (i >> 2) * 2]);
        mbar_wait(full0 + 8 * ((kTO + 2) % kStages), ((kTO + 2) / kStages) & 1);
#pragma unroll
        for (int i = 0; i < 8; i++) ldsm4t(w0[i], off[i & 3] + ((kTO + 2) % kStages) * kTileB + (i >> 2) * 2048);
#pragma unroll
        for (int i = 0; i < 8; i++) mma16816(d[i & 3], w0[i], b[8 + (i >> 2) * 2], b[9 + (i >> 2) * 2]);
        const float v0 = fmaf(ga, fsel(q0, d[0][0], fsel(q1, d[1][2], d[3][0])), f0);
        const float v1 = fmaf(ga, fsel(q0, d[0][2], fsel(q1, d[2][0], d[3][2])), f1);
        const float v2 = fmaf(ga, fsel(q0, d[1][0], d[2][2]), f2);
        if (tqp < 3) {
            const float4 old = atom_add4(slot, v0, v1, v2, 1.0f);
            if (old.w == (float)(kCTAs / 2 - 1)) {
                st_bf16(o, old.x + v0);
                st_bf16(o + 8, old.y + v1);
                if (tqp < 2) st_bf16(o + 16, old.z + v2);
            }
        }
    }
}

typedef CUresult (*EncodeFn)(CUtensorMap*, CUtensorMapDataType, cuuint32_t, void*, const cuuint64_t*, const cuuint64_t*,
                             const cuuint32_t*, const cuuint32_t*, CUtensorMapInterleave, CUtensorMapSwizzle,
                             CUtensorMapL2promotion, CUtensorMapFloatOOBfill);

void make_map(EncodeFn fn, CUtensorMap* m, void* base, int rows, int cols, int box_rows) {
    const cuuint64_t dims[3] = {64, (cuuint64_t)(cols / 64), (cuuint64_t)rows};
    const cuuint64_t strides[2] = {128, (cuuint64_t)cols * 2};
    const cuuint32_t box[3] = {64, 3, (cuuint32_t)box_rows};
    const cuuint32_t estr[3] = {1, 1, 1};
    fn(m, CU_TENSOR_MAP_DATA_TYPE_BFLOAT16, 3, base, dims, strides, box, estr, CU_TENSOR_MAP_INTERLEAVE_NONE,
       CU_TENSOR_MAP_SWIZZLE_128B, CU_TENSOR_MAP_L2_PROMOTION_NONE, CU_TENSOR_MAP_FLOAT_OOB_FILL_NONE);
}

void make_map_out(EncodeFn fn, CUtensorMap* m, void* base, int rows, int box_rows) {
    const cuuint64_t dims[3] = {64, (cuuint64_t)rows, (cuuint64_t)(kD / 64)};
    const cuuint64_t strides[2] = {(cuuint64_t)kOutRowB, 128};
    const cuuint32_t box[3] = {64, (cuuint32_t)box_rows, 5};
    const cuuint32_t estr[3] = {1, 1, 1};
    fn(m, CU_TENSOR_MAP_DATA_TYPE_BFLOAT16, 3, base, dims, strides, box, estr, CU_TENSOR_MAP_INTERLEAVE_NONE,
       CU_TENSOR_MAP_SWIZZLE_128B, CU_TENSOR_MAP_L2_PROMOTION_NONE, CU_TENSOR_MAP_FLOAT_OOB_FILL_NONE);
}

}

extern "C" void kernel_launch(void* const* d_in, const int* in_sizes, int n_in, void* d_out, int out_size) {
    (void)in_sizes; (void)n_in; (void)out_size;
    static EncodeFn encode = nullptr;
    static void* scratch = nullptr;
    if (!encode) {
        cudaGetSymbolAddress(&scratch, g_scratch);
        void* fn = nullptr;
        cudaDriverEntryPointQueryResult qr;
        cudaGetDriverEntryPoint("cuTensorMapEncodeTiled", &fn, cudaEnableDefault, &qr);
        encode = (EncodeFn)fn;
        cudaFuncSetAttribute(fused_decode_kernel, cudaFuncAttributeMaxDynamicSharedMemorySize, (int)sizeof(Smem));
    }
    Params p;
    make_map(encode, &p.tq, d_in[3], kD, kH * kDh, 32);
    make_map(encode, &p.tg, d_in[6], kD, kF, 16);
    make_map(encode, &p.tu, d_in[7], kD, kF, 16);
    make_map(encode, &p.tv, d_in[2], kH * kSk, kDh, kTileKeys);
    p.x = (const __nv_bfloat16*)d_in[0];
    p.k = (const unsigned char*)d_in[1];
    make_map_out(encode, &p.td, d_in[8], kF, kFC);
    make_map_out(encode, &p.to, d_in[4], kH * kDh, 32);
    p.gate_w = (const __nv_bfloat16*)d_in[9];
    p.out = (__nv_bfloat16*)d_out;
    p.g = (Scratch*)scratch;
    fused_decode_kernel<<<kCTAs, kThreads, sizeof(Smem), cudaStreamPerThread>>>(p);
}
```

```cpp
#include <cuda_runtime.h>
#include <cuda_bf16.h>
#include <cuda.h>
#include <stdint.h>

namespace {

constexpr int kD = 640;
constexpr int kH = 32;
constexpr int kDh = 192;
constexpr int kSk = 32768;
constexpr int kW = 4096;
constexpr int kF = 1536;
constexpr int kCTAs = 128;
constexpr int kGrp = 64;
constexpr int kGH = kH * kGrp / kCTAs;
constexpr int kCW = 8;
constexpr int kThreads = kCW * 32 + 64;
constexpr int kTileKeys = kW / kGrp;
constexpr int kRowB = kDh * 2;
constexpr int kTileB = kTileKeys * kRowB;
constexpr int kStages = 8;
constexpr int kOutRowB = kD * 2;
constexpr int kFC = 2 * kF / kCTAs;
constexpr int kOC = 2 * kH * kDh / kCTAs;
constexpr int kXR = kD / 4;
constexpr int kFR = kD / 8;
constexpr int kTQ = 0;
constexpr int kTK = 3;
constexpr int kTF = kTK + kGH;
constexpr int kTV = kTF + 2;
constexpr int kTD = kTV + kGH;
constexpr int kTO = kTD + 1;
constexpr int kNumTiles = kTO + 3;
constexpr int kSlots = 240;
#define NLATE 4
constexpr int kLate = NLATE;
static_assert(kLate >= 1 && kLate <= 4, "");
constexpr int kOSlots = kDh / 2;
constexpr int kAccSlots = kSlots + 2 * kLate * kOSlots;
constexpr unsigned kSpinLimit = 1u << 24;

#define WINDOW 71000
#define BIAS0 16
#define BIAS1 72
#define BIAS2 128
#define BALSTART 8
#define QDELAY 1000
#define MILE 576
#define MILE_LATE 384
#define EXP_PURE 0
constexpr uint32_t kWindow = WINDOW;

constexpr int kCbQ = kGH * kTileKeys, kCbF = kCbQ + kXR, kCbLen = kCbF + kFR;

struct Smem {
    alignas(1024) unsigned char ring[kStages][kTileB];
    alignas(16) float q[kGH][kDh];
    alignas(16) float sc[kGH][kTileKeys];
    alignas(16) __nv_bfloat16 rowc[kCbLen];
    alignas(16) __nv_bfloat16 coef[128];
    alignas(16) float part[4][kOC];
    float wgt[kGrp];
    float lscale[kLate];
    float stat[2 * kGH];
    float gate[2];
    unsigned tag;
    alignas(8) unsigned long long full[kStages];
    alignas(8) unsigned long long empty[kStages];
    alignas(8) unsigned long long coef_ready;
    alignas(8) unsigned long long go[2];
};

struct Scratch {
    alignas(256) unsigned epoch;
    alignas(256) unsigned accflag;
    alignas(256) unsigned prog;
    alignas(256) float4 acc[(kSlots + 8 * kOSlots) * 4];
    alignas(256) unsigned stat[kCTAs][2 * kGH];
    alignas(256) unsigned qmail[kCTAs][kDh];
    alignas(256) unsigned fmail[kCTAs][kDh];
    alignas(256) unsigned omail[kGH - 1][kCTAs][kDh];
};
__device__ Scratch g_scratch;

#define TSTAMP(i) do {} while (0)

__device__ __forceinline__ uint32_t s2u(const void* p) { return (uint32_t)__cvta_generic_to_shared(p); }

__device__ __forceinline__ void mbar_init(uint32_t bar, uint32_t cnt) {
    asm volatile("mbarrier.init.shared::cta.b64 [%0], %1;" ::"r"(bar), "r"(cnt) : "memory");
}
__device__ __forceinline__ void mbar_expect_tx(uint32_t bar, uint32_t bytes) {
    asm volatile("mbarrier.arrive.expect_tx.shared::cta.b64 _, [%0], %1;" ::"r"(bar), "r"(bytes) : "memory");
}
__device__ __forceinline__ void mbar_arrive(uint32_t bar, uint32_t cnt = 1) {
    asm volatile("mbarrier.arrive.shared::cta.b64 _, [%0], %1;" ::"r"(bar), "r"(cnt) : "memory");
}
__device__ __forceinline__ void mbar_wait(uint32_t bar, uint32_t parity) {
    asm volatile("{\n.reg .pred p;\n.reg .u32 n;\nmov.u32 n, 0;\n"
                 "WL:\nmbarrier.try_wait.parity.shared::cta.b64 p, [%0], %1;\n@p bra WD;\n"
                 "add.u32 n, n, 1;\nsetp.lt.u32 p, n, %2;\n@p bra WL;\ntrap;\nWD:\n}"
                 ::"r"(bar), "r"(parity), "n"(kSpinLimit) : "memory");
}
__device__ __forceinline__ bool mbar_test(uint32_t bar, uint32_t parity) {
    uint32_t ok;
    asm volatile("{\n.reg .pred p;\nmbarrier.test_wait.parity.shared::cta.b64 p, [%1], %2;\nselp.u32 %0, 1, 0, p;\n}"
                 : "=r"(ok) : "r"(bar), "r"(parity) : "memory");
    return ok != 0;
}
__device__ __forceinline__ void bulk_g2s(uint32_t dst, const void* src, uint32_t bytes, uint32_t bar, uint64_t pol) {
    asm volatile("cp.async.bulk.shared::cluster.global.mbarrier::complete_tx::bytes.L2::cache_hint [%0], [%1], %2, [%3], %4;"
                 ::"r"(dst), "l"(src), "r"(bytes), "r"(bar), "l"(pol) : "memory");
}
__device__ __forceinline__ void tma_3d(uint32_t dst, const CUtensorMap* map, int c1, int c2, uint32_t bar, uint64_t pol) {
    asm volatile("cp.async.bulk.tensor.3d.shared::cluster.global.mbarrier::complete_tx::bytes.L2::cache_hint [%0], [%1, {%4, %3, %6}], [%2], %5;"
                 ::"r"(dst), "l"(map), "r"(bar), "r"(c1), "r"(0), "l"(pol), "r"(c2) : "memory");
}
__device__ __forceinline__ void ldsm4t(uint32_t (&r)[4], uint32_t a) {
    asm volatile("ldmatrix.sync.aligned.m8n8.x4.trans.shared.b16 {%0,%1,%2,%3}, [%4];"
                 : "=r"(r[0]), "=r"(r[1]), "=r"(r[2]), "=r"(r[3]) : "r"(a));
}
__device__ __forceinline__ void mma16816(float (&d)[4], const uint32_t (&a)[4], uint32_t b0, uint32_t b1) {
    asm volatile("mma.sync.aligned.m16n8k16.row.col.f32.bf16.bf16.f32 {%0,%1,%2,%3}, {%4,%5,%6,%7}, {%8,%9}, {%0,%1,%2,%3};"
                 : "+f"(d[0]), "+f"(d[1]), "+f"(d[2]), "+f"(d[3]) : "r"(a[0]), "r"(a[1]), "r"(a[2]), "r"(a[3]), "r"(b0), "r"(b1));
}
__device__ __forceinline__ uint4 ldg128(const void* p) {
    uint4 v;
    asm volatile("ld.global.nc.v4.u32 {%0,%1,%2,%3}, [%4];" : "=r"(v.x), "=r"(v.y), "=r"(v.z), "=r"(v.w) : "l"(p));
    return v;
}
__device__ __forceinline__ uint4 lds128(uint32_t a) {
    uint4 v;
    asm volatile("ld.shared.v4.u32 {%0,%1,%2,%3}, [%4];" : "=r"(v.x), "=r"(v.y), "=r"(v.z), "=r"(v.w) : "r"(a));
    return v;
}

__device__ __forceinline__ void word_st(unsigned* p, float v, unsigned tag) {
    asm volatile("st.relaxed.gpu.global.u32 [%0], %1;" ::"l"(p), "r"((__float_as_uint(v) & ~3u) | tag) : "memory");
}
__device__ __forceinline__ float word_val(unsigned w) { return __uint_as_float(w & ~3u); }
struct Chunk {
    unsigned long long lo, hi;
    __device__ __forceinline__ float v(int i) const {
        const unsigned long long w = i < 2 ? lo : hi;
        return word_val((i & 1) ? (unsigned)(w >> 32) : (unsigned)w);
    }
};
__device__ __forceinline__ unsigned mail_poll1(const unsigned* p) {
    unsigned r;
    asm volatile("atom.relaxed.gpu.global.or.b32 %0, [%1], 0;" : "=r"(r) : "l"(p) : "memory");
    return r;
}
__device__ __forceinline__ void mail_poll4(const unsigned* p, Chunk& r) {
    asm volatile("atom.relaxed.gpu.global.or.b64 %0, [%2], 0;\natom.relaxed.gpu.global.or.b64 %1, [%2+8], 0;"
                 : "=l"(r.lo), "=l"(r.hi) : "l"(p) : "memory");
}
template <int N, int NP = N>
__device__ __forceinline__ void mail_gather(const unsigned* const (&p)[N / NP], int stride, unsigned tag, Chunk (&r)[N]) {
    const unsigned long long tag2 = tag * 0x100000001ull, mask = 0x300000003ull;
#pragma unroll
    for (int i = 0; i < N; i++) {
        asm volatile("ld.relaxed.gpu.global.v2.b64 {%0,%1}, [%2];"
                     : "=l"(r[i].lo), "=l"(r[i].hi) : "l"(p[i / NP] + (i % NP) * stride) : "memory");
    }
    unsigned n = 0;
#pragma unroll 1
    while (true) {
        unsigned bad = 0;
#pragma unroll
        for (int i = 0; i < N; i++) bad |= (((r[i].lo ^ tag2) | (r[i].hi ^ tag2)) & mask) ? 1u << i : 0u;
        bad = __reduce_or_sync(0xffffffffu, bad);
        if (bad == 0) break;
        __nanosleep(200);
#pragma unroll
        for (int i = 0; i < N; i++) if (bad >> i & 1) mail_poll4(p[i / NP] + (i % NP) * stride, r[i]);
        if (++n > kSpinLimit) __trap();
    }
}
__device__ __forceinline__ void word_wait(const unsigned* p, unsigned tag) {
    unsigned n = 0;
    while ((mail_poll1(p) ^ tag) & 3u) { __nanosleep(100); if (++n > kSpinLimit) __trap(); }
}

__device__ __forceinline__ float4 atom_add4(float4* p, float a, float b, float c, float d) {
    float4 r;
    asm volatile("atom.relaxed.gpu.global.add.v4.f32 {%0,%1,%2,%3}, [%4], {%5,%6,%7,%8};"
                 : "=f"(r.x), "=f"(r.y), "=f"(r.z), "=f"(r.w) : "l"(p), "f"(a), "f"(b), "f"(c), "f"(d) : "memory");
    return r;
}
__device__ __forceinline__ float4* acc_slot(Scratch* g, int i) { return &g->acc[(i >> 2) * 16 + (i & 3)]; }

enum { kBarCons = 1, kBarStart = 2, kBarStats = 3, kBarScalars = 4, kBarTeam = 5, kBarInit = 6 };
__device__ __forceinline__ void bar_sync(int id, int n) { asm volatile("bar.sync %0, %1;" ::"r"(id), "r"(n) : "memory"); }
__device__ __forceinline__ void bar_arrive(int id, int n) { asm volatile("bar.arrive %0, %1;" ::"r"(id), "r"(n) : "memory"); }

__device__ __forceinline__ void st_bf16(__nv_bfloat16* p, float v) {
    asm volatile("st.global.u16 [%0], %1;" ::"l"(p), "h"(__bfloat16_as_ushort(__float2bfloat16_rn(v))) : "memory");
}
__device__ __forceinline__ float fsel(bool c, float a, float b) {
    float r;
    asm("{\n.reg .pred p;\nsetp.ne.u32 p, %3, 0;\nselp.f32 %0, %1, %2, p;\n}" : "=f"(r) : "f"(a), "f"(b), "r"((unsigned)c));
    return r;
}
__device__ __forceinline__ float bf_lo(uint32_t w) { return __uint_as_float(w << 16); }
__device__ __forceinline__ float bf_hi(uint32_t w) { return __uint_as_float(w & 0xffff0000u); }
__device__ __forceinline__ float bfr(float v) { return __bfloat162float(__float2bfloat16_rn(v)); }
__device__ __forceinline__ uint32_t pack_bf16(float lo, float hi) {
    const __nv_bfloat162 v = __floats2bfloat162_rn(lo, hi);
    return *reinterpret_cast<const uint32_t*>(&v);
}
__device__ __forceinline__ float dot8(const float4& qa, const float4& qb, const uint4& v) {
    float a = qa.x * bf_lo(v.x), b = qa.y * bf_hi(v.x);
    a = fmaf(qa.z, bf_lo(v.y), a); b = fmaf(qa.w, bf_hi(v.y), b);
    a = fmaf(qb.x, bf_lo(v.z), a); b = fmaf(qb.y, bf_hi(v.z), b);
    a = fmaf(qb.z, bf_lo(v.w), a); b = fmaf(qb.w, bf_hi(v.w), b);
    return a + b;
}
__device__ __forceinline__ bool elect_one() {
    uint32_t ok;
    asm volatile("{\n.reg .pred p;\nelect.sync _|p, 0xffffffff;\nselp.u32 %0, 1, 0, p;\n}" : "=r"(ok));
    return ok != 0;
}

__host__ __device__ constexpr uint32_t tile_bytes(int t) {
    return (t == kTQ + 2 || t == kTF + 1) ? 32 * kRowB
         : t == kTF ? 48 * kRowB
         : t == kTD ? kFC * kOutRowB / 2
         : t >= kTO ? 32 * kOutRowB / 2 : kTileB;
}
constexpr uint64_t pack_back(int first) {
    uint64_t r = 0;
    for (int t = first; t < first + 21 && t < kNumTiles; t++) {
        uint32_t sum = 0;
        int j = t;
        for (; j >= 0; j--) { sum += tile_bytes(j); if (sum > kWindow) break; }
        r |= (uint64_t)(t - j > 5 ? 5 : t - j) << (3 * (t - first));
    }
    return r;
}
constexpr uint64_t kBackA = pack_back(0), kBackB = pack_back(21);
__device__ __forceinline__ int look_back(int t) {
    return (int)(((t < 21 ? kBackA : kBackB) >> (3 * (t < 21 ? t : t - 21))) & 7);
}

struct Params {
    const __nv_bfloat16* x;
    const unsigned char* k;
    const __nv_bfloat16* gate_w;
    __nv_bfloat16* out;
    Scratch* g;
    CUtensorMap tq;
    CUtensorMap tg;
    CUtensorMap tu;
    CUtensorMap tv;
    CUtensorMap td;
    CUtensorMap to;
};

__global__ void __launch_bounds__(kThreads, 1) fused_decode_kernel(const __grid_constant__ Params p) {
    extern __shared__ __align__(1024) unsigned char smem_raw[];
    Smem& sm = *reinterpret_cast<Smem*>(smem_raw);
    const int tid = threadIdx.x;
    const int lane = tid & 31;
    const int warp = tid >> 5;
    const int cta = blockIdx.x;
    const int cta0 = cta & ~(kGrp - 1);
    const int hl = (cta >> 2) & (kGH - 1);
    const uint32_t ring0 = s2u(&sm.ring[0][0]);
    const uint32_t full0 = s2u(&sm.full[0]);
    const uint32_t empty0 = s2u(&sm.empty[0]);

    uint64_t pol;
    asm volatile("createpolicy.fractional.L2::evict_first.b64 %0, 1.0;" : "=l"(pol));
    if (warp == kCW && elect_one()) {
        TSTAMP(0);
#pragma unroll
        for (int i = 0; i < kTK; i++) mbar_init(full0 + 8 * i, 1);
        asm volatile("fence.mbarrier_init.release.cluster;" ::: "memory");
#pragma unroll
        for (int i = 0; i < kTK; i++) {
            const int row = (cta & 3) * kXR + i * 64;
            mbar_expect_tx(full0 + 8 * i, tile_bytes(i));
            tma_3d(ring0 + i * kTileB, &p.tq, (cta >> 2) * 3, row, full0 + 8 * i, pol);
            if (i < 2) tma_3d(ring0 + i * kTileB + 32 * kRowB, &p.tq, (cta >> 2) * 3, row + 32, full0 + 8 * i, pol);
        }
        TSTAMP(1);
    }
    __syncwarp();

    if (warp == kCW) {
        const bool leader = elect_one();
        bar_sync(kBarInit, 64);
        bar_arrive(kBarStart, kThreads);
        const int key0 = (cta >> 6) * kGH * kSk + (kSk - kW) + (cta & (kGrp - 1)) * kTileKeys;
        const unsigned char* src = p.k + (size_t)key0 * kRowB;
        constexpr unsigned kProgMax = (kNumTiles - kTK) * kCTAs - 1;
        unsigned prog = 0;
        constexpr int kNever = 1 << 30;
        int mile0 = (kTV - 1 - kTK) * kCTAs + MILE, mile1 = (kTV + hl - kTK) * kCTAs + (hl < kGH - kLate ? MILE : MILE_LATE);
#pragma unroll 1
        for (int t = kTK; t < kNumTiles; t++) {
            const uint32_t st = t % kStages;
            const uint32_t dst = ring0 + st * kTileB, bar = full0 + 8 * st;
            if (t >= kStages) mbar_wait(empty0 + 8 * st, ((t / kStages) - 1) & 1);
            if (leader) mbar_expect_tx(bar, tile_bytes(t));
            int need = t - look_back(t);
            if (t >= BALSTART) {
                const int gp = (int)__shfl_sync(0xffffffffu, prog, 0);
                const int lead = (t - kTK) * kCTAs - gp;
                need += (lead > BIAS2) - (lead <= BIAS1) - (lead <= BIAS0);
                const int seen = t == kNumTiles - 1 ? kNever - 1 : gp;
                if (seen >= mile0) { mile0 = kNever; if (leader) mbar_arrive(s2u(&sm.go[0])); }
                if (seen >= mile1) { mile1 = kNever; if (leader) mbar_arrive(s2u(&sm.go[1])); }
            }
            if (need >= 0) mbar_wait(full0 + 8 * (need % kStages), (need / kStages) & 1);
            if (leader) {
                if (t < kTF) {
                    bulk_g2s(dst, src, kTileB, bar, pol);
                } else if (t < kTV) {
                    const CUtensorMap* m = cta < 64 ? &p.tg : &p.tu;
                    const int row = (cta & 7) * kFR + (t - kTF) * 48, blk = ((cta >> 3) & 7) * 3;
                    tma_3d(dst, m, blk, row, bar, pol);
                    tma_3d(dst + 16 * kRowB, m, blk, row + 16, bar, pol);
                    if (t == kTF) tma_3d(dst + 32 * kRowB, m, blk, row + 32, bar, pol);
                } else if (t < kTD) {
                    tma_3d(dst, &p.tv, 0, key0 + (t - kTV) * kSk, bar, pol);
                } else {
                    tma_3d(dst, t == kTD ? &p.td : &p.to, t == kTD ? (cta >> 1) * kFC : (cta >> 1) * kOC + (t - kTO) * 32,
                           (cta & 1) * 5, bar, pol);
                }
                TSTAMP(16 + t);
            }
            src += (size_t)kSk * kRowB;
            if (lane == 0) {
                if (t + 1 >= BALSTART)
                    asm volatile("atom.relaxed.gpu.global.inc.u32 %0, [%1], %2;" : "=r"(prog) : "l"(&p.g->prog), "n"(kProgMax) : "memory");
                else
                    asm volatile("red.relaxed.gpu.global.inc.u32 [%0], %1;" ::"l"(&p.g->prog), "n"(kProgMax) : "memory");
            }
        }
        if (lane == 0 && prog == kProgMax) p.g->epoch = sm.tag;
        return;
    }

    unsigned tag;
    if (warp == kCW + 1) {
        if (elect_one()) {
#pragma unroll
            for (int i = 0; i < kStages; i++) { if (i >= kTK) mbar_init(full0 + 8 * i, 1); mbar_init(empty0 + 8 * i, kCW); }
            mbar_init(s2u(&sm.coef_ready), 2);
            mbar_init(s2u(&sm.go[0]), 1);
            mbar_init(s2u(&sm.go[1]), 1);
            asm volatile("fence.mbarrier_init.release.cluster;" ::: "memory");
        }
        __syncwarp();
        bar_arrive(kBarInit, 64);
        unsigned e = 0;
        if (lane == 31) asm volatile("ld.relaxed.gpu.global.u32 %0, [%1];" : "=r"(e) : "l"(&p.g->epoch) : "memory");
        if (lane < 30) {
            const uint4 v = ldg128(p.x + (lane < 20 ? (cta & 3) * kXR + lane * 8 : (cta & 7) * kFR + (lane - 20) * 8));
            *reinterpret_cast<uint4*>(&sm.rowc[kCbQ + lane * 8]) = v;
        }
        tag = __shfl_sync(0xffffffffu, e, 31) % 3u + 1u;
        if (lane == 0) sm.tag = tag;
        bar_arrive(kBarStart, kThreads);
        __nanosleep(3000);
        if (cta == 0) {
            for (int i = lane; i < kAccSlots; i += 32) *acc_slot(p.g, i) = make_float4(0.f, 0.f, 0.f, 0.f);
            __threadfence();
            __syncwarp();
            if (lane == 0) word_st(&p.g->accflag, 0.f, tag);
        }
        {
            float z = 0.f;
#pragma unroll 1
            for (int j = lane; j < kD / 8; j += 32) {
                const uint4 gx = ldg128(p.x + j * 8), gw = ldg128(p.gate_w + j * 8);
                z += bfr(bf_lo(gx.x) * bf_lo(gw.x)) + bfr(bf_hi(gx.x) * bf_hi(gw.x));
                z += bfr(bf_lo(gx.y) * bf_lo(gw.y)) + bfr(bf_hi(gx.y) * bf_hi(gw.y));
                z += bfr(bf_lo(gx.z) * bf_lo(gw.z)) + bfr(bf_hi(gx.z) * bf_hi(gw.z));
                z += bfr(bf_lo(gx.w) * bf_lo(gw.w)) + bfr(bf_hi(gx.w) * bf_hi(gw.w));
            }
#pragma unroll
            for (int o = 16; o > 0; o >>= 1) z += __shfl_xor_sync(0xffffffffu, z, o);
            const float gate = bfr(1.0f / (1.0f + __expf(-bfr(z))));
            if (lane == 0) { sm.gate[0] = gate; sm.gate[1] = bfr(1.0f - gate); }
            if (lane < 8) sm.coef[kOC + kFC + lane] = __float2bfloat16_rn(0.f);
        }
        __nanosleep(2000);
        if (lane == 0) {
            word_wait(&p.g->accflag, tag);
            __threadfence();
        }
        __syncwarp();
        bar_sync(kBarStats, 288);
        word_st(&p.g->stat[cta][lane], sm.stat[lane], tag);
        mbar_wait(s2u(&sm.go[0]), 0);
        {
            const int mtx = lane >> 4, rb = (lane >> 1) & 7, half = lane & 1;
            const unsigned* sa = p.g->stat[cta0 + lane];
            const unsigned* sb = p.g->stat[cta0 + 32 + lane];
            const unsigned* fm = &p.g->fmail[(mtx * 8 + (cta >> 4)) * 8 + rb][((cta >> 1) & 7) * kFC + half * 12];
            const unsigned* const ps[9] = {sa + (hl >> 1) * 4, sb + (hl >> 1) * 4, sa + 24, sb + 24, sa + 28, sb + 28, fm, fm + 4, fm + 8};
            Chunk r[9];
            mail_gather<9, 1>(ps, 0, tag, r);
#pragma unroll 1
            for (int i = -1; i < kLate; i++) {
                const int hd = i < 0 ? hl : kGH - kLate + i;
                const Chunk a = i < 0 ? r[0] : hd < 14 ? r[2] : r[4], b = i < 0 ? r[1] : hd < 14 ? r[3] : r[5];
                const float m0 = hd & 1 ? a.v(2) : a.v(0), l0 = hd & 1 ? a.v(3) : a.v(1);
                const float m1 = hd & 1 ? b.v(2) : b.v(0), l1 = hd & 1 ? b.v(3) : b.v(1);
                float M = fmaxf(m0, m1);
#pragma unroll
                for (int o = 16; o > 0; o >>= 1) M = fmaxf(M, __shfl_xor_sync(0xffffffffu, M, o));
                const float w0 = __expf(m0 - M), w1 = __expf(m1 - M);
                float L = w0 * l0 + w1 * l1;
#pragma unroll
                for (int o = 16; o > 0; o >>= 1) L += __shfl_xor_sync(0xffffffffu, L, o);
                if (i < 0) { sm.wgt[lane] = w0 / L; sm.wgt[lane + 32] = w1 / L; }
                else if (lane == (cta & 31)) sm.lscale[i] = ((cta & 32) ? w1 : w0) / L;
            }
#pragma unroll
            for (int j = 0; j < 12; j++) {
                float v = r[6 + (j >> 2)].v(j & 3);
                v += __shfl_xor_sync(0xffffffffu, v, 2);
                v += __shfl_xor_sync(0xffffffffu, v, 4);
                v += __shfl_xor_sync(0xffffffffu, v, 8);
                const float gt = bfr(v);
                const float up = __shfl_xor_sync(0xffffffffu, gt, 16);
                if (lane < 2) sm.coef[kOC + half * 12 + j] = __float2bfloat16_rn((gt > 0.f ? gt : gt * 0.f) * up);
            }
        }
        if (lane == 0) TSTAMP(10);
        bar_arrive(kBarScalars, 224);
    } else {
        bar_sync(kBarStart, kThreads);
        tag = sm.tag;
        if (tid == 0) TSTAMP(2);

        const int mg = lane >> 2, tq = lane & 3;
        const int lk = (lane & 7) + ((lane >> 4) << 3);
        uint32_t voff[2];
#pragma unroll
        for (int i = 0; i < 2; i++) {
            const int line = lk * 3 + (warp >> 1);
            voff[i] = line * 128 + (((((warp & 1) * 4 + 2 * i + ((lane >> 3) & 1)) ^ line) & 7) << 4);
        }
#pragma unroll 1
        for (int pass = 0; pass < 3; pass++) {
            if (warp < 6) {
                const int t0 = pass == 0 ? kTQ : (pass == 1 ? kTF : kTV);
                const int t1 = pass == 0 ? kTK : (pass == 1 ? kTV : kTD);
                const uint32_t* cf = reinterpret_cast<const uint32_t*>(&sm.rowc[pass == 0 ? kCbQ : (pass == 1 ? kCbF : 0)]) + tq;
                float d[4][4];
#pragma unroll
                for (int i = 0; i < 4; i++) d[i][0] = d[i][1] = d[i][2] = d[i][3] = 0.f;
#pragma unroll 1
                for (int t = t0; t < t1; t++) {
                    const uint32_t st = t % kStages;
                    const int nk = tile_bytes(t) / (16 * kRowB);
                    if (t == kTD - kLate) bar_sync(kBarScalars, 224);
                    uint32_t b[8];
#pragma unroll
                    for (int j = 0; j < 8; j++) b[j] = cf[j * 4];
                    cf += nk * 8;
                    const bool late = t >= kTD - kLate;
                    const float ls = sm.lscale[late ? t - (kTD - kLate) : 0];
                    void* dst = late ? (void*)acc_slot(p.g, kSlots + ((cta >> 6) * kLate + t - (kTD - kLate)) * kOSlots + warp * 16 + mg * 2 + (tq >> 1))
                                     : (void*)((t < kTK ? p.g->qmail[cta] : t < kTV ? p.g->fmail[cta] : p.g->omail[t - kTV][cta]) + warp * 32 + tq * 8 + mg);
                    mbar_wait(full0 + 8 * st, (t / kStages) & 1);
                    const uint32_t a = ring0 + st * kTileB;
                    uint32_t w[8][4];
#pragma unroll
                    for (int j = 0; j < 4; j++) ldsm4t(w[j], a + voff[j & 1] + (j >> 1) * (16 * kRowB));
                    if (nk > 2) {
                        ldsm4t(w[4], a + voff[0] + 2 * (16 * kRowB));
                        ldsm4t(w[5], a + voff[1] + 2 * (16 * kRowB));
                    }
                    if (nk > 3) {
                        ldsm4t(w[6], a + voff[0] + 3 * (16 * kRowB));
                        ldsm4t(w[7], a + voff[1] + 3 * (16 * kRowB));
                    }
#pragma unroll
                    for (int j = 0; j < 4; j++) mma16816(d[j], w[j], b[(j >> 1) * 2], b[(j >> 1) * 2 + 1]);
                    if (nk > 2) { mma16816(d[0], w[4], b[4], b[5]); mma16816(d[1], w[5], b[4], b[5]); }
                    if (nk > 3) { mma16816(d[2], w[6], b[6], b[7]); mma16816(d[3], w[7], b[6], b[7]); }
                    if (pass == 2 || t == t1 - 1) {
                        const float c0 = fsel(tq & 2, d[1][0] + d[3][0], d[0][0] + d[2][0]);
                        const float c8 = fsel(tq & 2, d[1][2] + d[3][2], d[0][2] + d[2][2]);
                        if (!late) word_st((unsigned*)dst, fsel(tq & 1, c8, c0), tag);
                        else if (!(tq & 1))
                            asm volatile("red.relaxed.gpu.global.add.v4.f32 [%0], {%1,%2,%3,%4};"
                                         ::"l"(dst), "f"(c0 * ls), "f"(c8 * ls), "f"(0.f), "f"(1.f) : "memory");
#pragma unroll
                        for (int i = 0; i < 4; i++) d[i][0] = d[i][1] = d[i][2] = d[i][3] = 0.f;
                    }
                    __syncwarp();
                    if (lane == 0) mbar_arrive(empty0 + 8 * st, warp < 2 ? 2 : 1);
                }
                if (tid == 0) TSTAMP(3 + pass);
            }
            if (pass == 1) bar_sync(kBarStats, 288);
            if (pass != 0) continue;

            if (warp >= 6) {
                mbar_wait(full0 + 8 * (kTK - 1), 0);
                __nanosleep(QDELAY);
                word_wait(&p.g->qmail[cta0 + tid - 192][kDh - 1], tag);
            }
            bar_sync(kBarCons, 256);
            {
                Chunk r[12];
                const unsigned* ps_[3];
#pragma unroll
                for (int k = 0; k < 3; k++) {
                    const int id = tid + 256 * k, j = id / 48;
                    ps_[k] = &p.g->qmail[cta0 + j * 4][(id - j * 48) * 4];
                }
                const unsigned* const ps[3] = {ps_[0], ps_[1], ps_[2]};
                mail_gather<12, 4>(ps, kDh, tag, r);
#pragma unroll
                for (int k = 0; k < 3; k++) {
                    float v[4];
#pragma unroll
                    for (int e = 0; e < 4; e++) v[e] = bfr((r[k * 4].v(e) + r[k * 4 + 1].v(e)) + (r[k * 4 + 2].v(e) + r[k * 4 + 3].v(e)));
                    reinterpret_cast<float4*>(&sm.q[0][0])[tid + 256 * k] = make_float4(v[0], v[1], v[2], v[3]);
                }
            }
            bar_sync(kBarCons, 256);
            if (tid == 0) TSTAMP(6);

            {
                const int g = lane >> 3, c = lane & 7;
                const uint32_t lane_off = (uint32_t)((warp * 8 + g) * kRowB + c * 16);
                const float scale = 0.07216878364870322f;
#pragma unroll 1
                for (int j = 0; j < kGH; j++) {
                    const int t = kTK + j;
                    const uint32_t st = t % kStages;
                    float4 q[6];
#pragma unroll
                    for (int i = 0; i < 6; i++) q[i] = *reinterpret_cast<const float4*>(&sm.q[j][(i >> 1) * 64 + c * 8 + (i & 1) * 4]);
                    mbar_wait(full0 + 8 * st, (t / kStages) & 1);
                    const uint32_t a = ring0 + st * kTileB + lane_off;
                    uint4 v[6];
#pragma unroll
                    for (int i = 0; i < 3; i++) { v[i] = lds128(a + i * 128); v[3 + i] = lds128(a + 4 * kRowB + i * 128); }
                    const float s0 = dot8(q[0], q[1], v[0]) + dot8(q[2], q[3], v[1]) + dot8(q[4], q[5], v[2]);
                    const float s1 = dot8(q[0], q[1], v[3]) + dot8(q[2], q[3], v[4]) + dot8(q[4], q[5], v[5]);
                    __syncwarp();
                    if (lane == 0) mbar_arrive(empty0 + 8 * st);
                    float mine = (c & 4) ? s1 : s0;
                    const float other = (c & 4) ? s0 : s1;
                    mine += __shfl_xor_sync(0xffffffffu, other, 4);
                    mine += __shfl_xor_sync(0xffffffffu, mine, 2);
                    mine += __shfl_xor_sync(0xffffffffu, mine, 1);
                    if ((c & 3) == 0) sm.sc[j][warp * 8 + c + g] = bfr(bfr(mine) * scale);
                }
            }
            if (tid == 0) TSTAMP(7);
            bar_sync(kBarCons, 256);
            {
                float4 sv = *reinterpret_cast<const float4*>(&sm.sc[0][tid * 4]);
                float m = fmaxf(fmaxf(sv.x, sv.y), fmaxf(sv.z, sv.w));
#pragma unroll
                for (int o = 8; o > 0; o >>= 1) m = fmaxf(m, __shfl_xor_sync(0xffffffffu, m, o));
                sv.x = __expf(sv.x - m); sv.y = __expf(sv.y - m); sv.z = __expf(sv.z - m); sv.w = __expf(sv.w - m);
                *reinterpret_cast<uint2*>(&sm.rowc[tid * 4]) = make_uint2(pack_bf16(sv.x, sv.y), pack_bf16(sv.z, sv.w));
                float l = (sv.x + sv.y) + (sv.z + sv.w);
#pragma unroll
                for (int o = 8; o > 0; o >>= 1) l += __shfl_xor_sync(0xffffffffu, l, o);
                if ((lane & 15) == 0) { sm.stat[(tid >> 4) * 2] = m; sm.stat[(tid >> 4) * 2 + 1] = l; }
            }
        }

        if (warp < 5) {
            const uint32_t* cw = reinterpret_cast<const uint32_t*>(sm.coef);
            int tqp = tq;
            asm volatile("" : "+r"(tqp));
            const bool q0 = tqp == 0, q1 = tqp == 1;
            float4* slot = acc_slot(p.g, (((cta & 1) * 5 + warp) * 8 + mg) * 3 + tq);
            __nv_bfloat16* o = p.out + ((cta & 1) * 5 + warp) * 64 + tq * 24 + mg;
            float d[4][4];
            uint32_t off[4], w0[8][4], w1[8][4];
            float f0, f1, f2;
#pragma unroll
            for (int i = 0; i < 4; i++) off[i] = lk * 128 + ((((2 * i + ((lane >> 3) & 1)) ^ lk) & 7) << 4);
            {
                const uint32_t b0 = cw[48 + tq], b1 = cw[52 + tq], b2 = cw[56 + tq], b3 = cw[60 + tq];
                const float gb = sm.gate[1];
                const uint32_t a = ring0 + (kTD % kStages) * kTileB + warp * kFC * 128;
                mbar_wait(full0 + 8 * (kTD % kStages), (kTD / kStages) & 1);
#pragma unroll
                for (int i = 0; i < 4; i++) {
                    ldsm4t(w0[i], a + off[i]);
                    ldsm4t(w0[4 + i], a + off[i] + (lane < 16 ? 16 : 8) * 128);
                }
#pragma unroll
                for (int i = 0; i < 4; i++) {
                    d[i][0] = d[i][1] = d[i][2] = d[i][3] = 0.f;
                    mma16816(d[i], w0[i], b0, b1);
                    mma16816(d[i], w0[4 + i], b2, b3);
                }
                f0 = gb * fsel(q0, d[0][0], fsel(q1, d[1][2], d[3][0]));
                f1 = gb * fsel(q0, d[0][2], fsel(q1, d[2][0], d[3][2]));
                f2 = gb * fsel(q0, d[1][0], d[2][2]);
            }
#pragma unroll
            for (int i = 0; i < 4; i++) off[i] += ring0 + warp * 32 * 128;
            asm volatile("" : "+r"(off[0]), "+r"(off[1]), "+r"(off[2]), "+r"(off[3]));
            mbar_wait(full0 + 8 * (kTO % kStages), (kTO / kStages) & 1);
#pragma unroll
            for (int i = 0; i < 8; i++) ldsm4t(w0[i], off[i & 3] + (kTO % kStages) * kTileB + (i >> 2) * 2048);
            uint32_t b[12];
            float ga = sm.gate[0];
#pragma unroll
            for (int i = 0; i < 4; i++) d[i][0] = d[i][1] = d[i][2] = d[i][3] = 0.f;
            const bool early = __all_sync(0xffffffffu, mbar_test(s2u(&sm.coef_ready), 0));
            if (early) {
#pragma unroll
                for (int j = 0; j < 12; j++) b[j] = cw[j * 4 + tq];
#pragma unroll
                for (int i = 0; i < 8; i++) mma16816(d[i & 3], w0[i], b[(i >> 2) * 2], b[(i >> 2) * 2 + 1]);
            }
            asm volatile("" : "+l"(slot), "+l"(o), "+f"(ga), "+f"(f0), "+f"(f1), "+f"(f2));
            mbar_wait(full0 + 8 * ((kTO + 1) % kStages), ((kTO + 1) / kStages) & 1);
#pragma unroll
            for (int i = 0; i < 8; i++) ldsm4t(w1[i], off[i & 3] + ((kTO + 1) % kStages) * kTileB + (i >> 2) * 2048);
            if (!early) {
                mbar_wait(s2u(&sm.coef_ready), 0);
#pragma unroll
                for (int j = 0; j < 12; j++) b[j] = cw[j * 4 + tq];
#pragma unroll
                for (int i = 0; i < 8; i++) mma16816(d[i & 3], w0[i], b[(i >> 2) * 2], b[(i >> 2) * 2 + 1]);
            }
#pragma unroll
            for (int i = 0; i < 8; i++) mma16816(d[i & 3], w1[i], b[4 + (i >> 2) * 2], b[5 + (i >> 2) * 2]);
            mbar_wait(full0 + 8 * ((kTO + 2) % kStages), ((kTO + 2) / kStages) & 1);
#pragma unroll
            for (int i = 0; i < 8; i++) ldsm4t(w0[i], off[i & 3] + ((kTO + 2) % kStages) * kTileB + (i >> 2) * 2048);
#pragma unroll
            for (int i = 0; i < 8; i++) mma16816(d[i & 3], w0[i], b[8 + (i >> 2) * 2], b[9 + (i >> 2) * 2]);
            const float v0 = fmaf(ga, fsel(q0, d[0][0], fsel(q1, d[1][2], d[3][0])), f0);
            const float v1 = fmaf(ga, fsel(q0, d[0][2], fsel(q1, d[2][0], d[3][2])), f1);
            const float v2 = fmaf(ga, fsel(q0, d[1][0], d[2][2]), f2);
            if (tqp < 3) {
                const float4 old = atom_add4(slot, v0, v1, v2, 1.0f);
                if (old.w == (float)(kCTAs / 2 - 1)) {
                    st_bf16(o, old.x + v0);
                    st_bf16(o + 8, old.y + v1);
                    if (tqp < 2) st_bf16(o + 16, old.z + v2);
                }
            }
        }
        if (warp < 6) return;
    }

    {
        const int tt = warp == kCW + 1 ? 64 + lane : tid - 192;
        const int half = (cta >> 1) & 1;
        bar_sync(kBarTeam, 96);
        mbar_wait(s2u(&sm.go[1]), 0);
        if (hl >= kGH - kLate) {
            if (tt < kOC / 2) {
                float4* slot = acc_slot(p.g, kSlots + ((cta >> 6) * kLate + hl - (kGH - kLate)) * kOSlots + half * (kOC / 2) + tt);
                float4 r;
                unsigned n = 0;
                do { r = atom_add4(slot, 0.f, 0.f, 0.f, 0.f); if (++n > kSpinLimit) __trap(); } while (r.w != (float)kGrp);
                const int d = (tt >> 4) * 32 + (tt & 1) * 16 + ((tt >> 1) & 7);
                sm.coef[d] = __float2bfloat16_rn(r.x);
                sm.coef[d + 8] = __float2bfloat16_rn(r.y);
            }
        } else {
            const int c = tt % 24, sg = tt / 24;
            const unsigned* const ps[1] = {&p.g->omail[hl][cta0 + sg][half * kOC + c * 4]};
            Chunk r[16];
            mail_gather<16>(ps, 4 * kDh, tag, r);
            float4 acc = make_float4(0.f, 0.f, 0.f, 0.f);
#pragma unroll
            for (int k = 0; k < 16; k++) {
                const float w = sm.wgt[sg + 4 * k];
                acc.x = fmaf(w, r[k].v(0), acc.x); acc.y = fmaf(w, r[k].v(1), acc.y);
                acc.z = fmaf(w, r[k].v(2), acc.z); acc.w = fmaf(w, r[k].v(3), acc.w);
            }
            *reinterpret_cast<float4*>(&sm.part[sg][c * 4]) = acc;
            bar_sync(kBarTeam, 96);
            if (tt < kOC / 2) {
                const float2 a = *reinterpret_cast<const float2*>(&sm.part[0][tt * 2]), b = *reinterpret_cast<const float2*>(&sm.part[1][tt * 2]);
                const float2 e = *reinterpret_cast<const float2*>(&sm.part[2][tt * 2]), f = *reinterpret_cast<const float2*>(&sm.part[3][tt * 2]);
                reinterpret_cast<uint32_t*>(sm.coef)[tt] = pack_bf16((a.x + b.x) + (e.x + f.x), (a.y + b.y) + (e.y + f.y));
            }
        }
        __syncwarp();
        if (tt < 64 && lane == 0) { if (tt == 0) TSTAMP(8); mbar_arrive(s2u(&sm.coef_ready)); }
    }
}

typedef CUresult (*EncodeFn)(CUtensorMap*, CUtensorMapDataType, cuuint32_t, void*, const cuuint64_t*, const cuuint64_t*,
                             const cuuint32_t*, const cuuint32_t*, CUtensorMapInterleave, CUtensorMapSwizzle,
                             CUtensorMapL2promotion, CUtensorMapFloatOOBfill);

void make_map(EncodeFn fn, CUtensorMap* m, void* base, int rows, int cols, int box_rows) {
    const cuuint64_t dims[3] = {64, (cuuint64_t)(cols / 64), (cuuint64_t)rows};
    const cuuint64_t strides[2] = {128, (cuuint64_t)cols * 2};
    const cuuint32_t box[3] = {64, 3, (cuuint32_t)box_rows};
    const cuuint32_t estr[3] = {1, 1, 1};
    fn(m, CU_TENSOR_MAP_DATA_TYPE_BFLOAT16, 3, base, dims, strides, box, estr, CU_TENSOR_MAP_INTERLEAVE_NONE,
       CU_TENSOR_MAP_SWIZZLE_128B, CU_TENSOR_MAP_L2_PROMOTION_NONE, CU_TENSOR_MAP_FLOAT_OOB_FILL_NONE);
}
void make_map_out(EncodeFn fn, CUtensorMap* m, void* base, int rows, int box_rows) {
    const cuuint64_t dims[3] = {64, (cuuint64_t)rows, (cuuint64_t)(kD / 64)};
    const cuuint64_t strides[2] = {(cuuint64_t)kOutRowB, 128};
    const cuuint32_t box[3] = {64, (cuuint32_t)box_rows, 5};
    const cuuint32_t estr[3] = {1, 1, 1};
    fn(m, CU_TENSOR_MAP_DATA_TYPE_BFLOAT16, 3, base, dims, strides, box, estr, CU_TENSOR_MAP_INTERLEAVE_NONE,
       CU_TENSOR_MAP_SWIZZLE_128B, CU_TENSOR_MAP_L2_PROMOTION_NONE, CU_TENSOR_MAP_FLOAT_OOB_FILL_NONE);
}

}

extern "C" void kernel_launch(void* const* d_in, const int* in_sizes, int n_in, void* d_out, int out_size) {
    (void)in_sizes; (void)n_in; (void)out_size;
    static EncodeFn encode = nullptr;
    static void* scratch = nullptr;
    if (!encode) {
        cudaGetSymbolAddress(&scratch, g_scratch);
        void* fn = nullptr;
        cudaDriverEntryPointQueryResult qr;
        cudaGetDriverEntryPoint("cuTensorMapEncodeTiled", &fn, cudaEnableDefault, &qr);
        encode = (EncodeFn)fn;
        cudaFuncSetAttribute(fused_decode_kernel, cudaFuncAttributeMaxDynamicSharedMemorySize, (int)sizeof(Smem));
    }
    Params p;
    p.x = (const __nv_bfloat16*)d_in[0];
    p.k = (const unsigned char*)d_in[1];
    p.gate_w = (const __nv_bfloat16*)d_in[9];
    p.out = (__nv_bfloat16*)d_out;
    p.g = (Scratch*)scratch;
    make_map(encode, &p.tq, d_in[3], kD, kH * kDh, 32);
    make_map(encode, &p.tg, d_in[6], kD, kF, 16);
    make_map(encode, &p.tu, d_in[7], kD, kF, 16);
    make_map(encode, &p.tv, d_in[2], kH * kSk, kDh, kTileKeys);
    make_map_out(encode, &p.td, d_in[8], kF, kFC);
    make_map_out(encode, &p.to, d_in[4], kH * kDh, 32);
    fused_decode_kernel<<<kCTAs, kThreads, sizeof(Smem), cudaStreamPerThread>>>(p);
}
```

```cpp
#include <cuda_runtime.h>
#include <cuda_bf16.h>
#include <cuda.h>
#include <math.h>
#include <stdint.h>

namespace {

constexpr int kD = 640;
constexpr int kH = 32;
constexpr int kDh = 192;
constexpr int kSk = 32768;
constexpr int kW = 4096;
constexpr int kF = 1536;
constexpr int kCTAs = 128;
constexpr int kGrp = 64;
constexpr int kGH = kH * kGrp / kCTAs;
constexpr int kCW = 8;
constexpr int kThreads = kCW * 32 + 64;
constexpr int kTileKeys = kW / kGrp;
constexpr int kRowB = kDh * 2;
constexpr int kTileB = kTileKeys * kRowB;
constexpr int kStages = 8;
constexpr int kOutRowB = kD * 2;
constexpr int kFC = 2 * kF / kCTAs;
constexpr int kOC = 2 * kH * kDh / kCTAs;
constexpr int kXR = kD / 4;
constexpr int kFR = kD / 8;
constexpr int kTQ = 0;
constexpr int kTK = 3;
constexpr int kTF = kTK + kGH;
constexpr int kTV = kTF + 2;
constexpr int kTD = kTV + kGH;
constexpr int kTO = kTD + 1;
constexpr int kNumTiles = kTO + 3;
constexpr int kSlots = 240;
constexpr int kLate = 4;
constexpr int kOSlots = kDh / 2;
constexpr int kAccSlots = kSlots + 2 * kLate * kOSlots;
constexpr unsigned kSpinLimit = 1u << 24;
static_assert(kTD - kLate + kStages > kNumTiles - 1, "the producer must be able to finish before the late V tiles are consumed");

constexpr uint32_t kWindow = 71000;
constexpr int kBalStart = 8;
constexpr int kLead0 = 16, kLead1 = 72, kLead2 = 128;
constexpr int kMile = 576, kMileLate = 384;

constexpr int kCbQ = kGH * kTileKeys, kCbF = kCbQ + kXR, kCbLen = kCbF + kFR;

struct Smem {
    alignas(1024) unsigned char ring[kStages][kTileB];
    alignas(16) float q[kGH][kDh];
    alignas(16) float sc[kGH][kTileKeys];
    alignas(16) __nv_bfloat16 rowc[kCbLen];
    alignas(16) __nv_bfloat16 coef[128];
    alignas(16) float part[4][kOC];
    float wgt[kGrp];
    float lscale[kLate];
    float stat[2 * kGH];
    float gate[2];
    unsigned tag;
    alignas(8) unsigned long long full[kStages];
    alignas(8) unsigned long long empty[kStages];
    alignas(8) unsigned long long coef_ready;
    alignas(8) unsigned long long go[2];
};

struct Scratch {
    alignas(256) unsigned epoch;
    alignas(256) unsigned accflag;
    alignas(256) unsigned prog;
    alignas(256) float4 acc[kAccSlots * 4];
    alignas(256) unsigned stat[kCTAs][2 * kGH];
    alignas(256) unsigned qmail[kCTAs][kDh];
    alignas(256) unsigned fmail[kCTAs][kDh];
    alignas(256) unsigned omail[kGH - kLate][kCTAs][kDh];
};
__device__ Scratch g_scratch;

__device__ __forceinline__ uint32_t s2u(const void* p) { return (uint32_t)__cvta_generic_to_shared(p); }

__device__ __forceinline__ void mbar_init(uint32_t bar, uint32_t cnt) {
    asm volatile("mbarrier.init.shared::cta.b64 [%0], %1;" ::"r"(bar), "r"(cnt) : "memory");
}
__device__ __forceinline__ void mbar_expect_tx(uint32_t bar, uint32_t bytes) {
    asm volatile("mbarrier.arrive.expect_tx.shared::cta.b64 _, [%0], %1;" ::"r"(bar), "r"(bytes) : "memory");
}
__device__ __forceinline__ void mbar_arrive(uint32_t bar, uint32_t cnt = 1) {
    asm volatile("mbarrier.arrive.shared::cta.b64 _, [%0], %1;" ::"r"(bar), "r"(cnt) : "memory");
}
__device__ __forceinline__ void mbar_wait(uint32_t bar, uint32_t parity) {
    asm volatile("{\n.reg .pred p;\n.reg .u32 n;\nmov.u32 n, 0;\n"
                 "WL:\nmbarrier.try_wait.parity.shared::cta.b64 p, [%0], %1;\n@p bra WD;\n"
                 "add.u32 n, n, 1;\nsetp.lt.u32 p, n, %2;\n@p bra WL;\ntrap;\nWD:\n}"
                 ::"r"(bar), "r"(parity), "n"(kSpinLimit) : "memory");
}
__device__ __forceinline__ bool mbar_test(uint32_t bar, uint32_t parity) {
    uint32_t ok;
    asm volatile("{\n.reg .pred p;\nmbarrier.test_wait.parity.shared::cta.b64 p, [%1], %2;\nselp.u32 %0, 1, 0, p;\n}"
                 : "=r"(ok) : "r"(bar), "r"(parity) : "memory");
    return ok != 0;
}
__device__ __forceinline__ void bulk_g2s(uint32_t dst, const void* src, uint32_t bytes, uint32_t bar, uint64_t pol) {
    asm volatile("cp.async.bulk.shared::cluster.global.mbarrier::complete_tx::bytes.L2::cache_hint [%0], [%1], %2, [%3], %4;"
                 ::"r"(dst), "l"(src), "r"(bytes), "r"(bar), "l"(pol) : "memory");
}
__device__ __forceinline__ void tma_3d(uint32_t dst, const CUtensorMap* map, int c1, int c2, uint32_t bar, uint64_t pol) {
    asm volatile("cp.async.bulk.tensor.3d.shared::cluster.global.mbarrier::complete_tx::bytes.L2::cache_hint [%0], [%1, {%4, %3, %6}], [%2], %5;"
                 ::"r"(dst), "l"(map), "r"(bar), "r"(c1), "r"(0), "l"(pol), "r"(c2) : "memory");
}
__device__ __forceinline__ void ldsm4t(uint32_t (&r)[4], uint32_t a) {
    asm volatile("ldmatrix.sync.aligned.m8n8.x4.trans.shared.b16 {%0,%1,%2,%3}, [%4];"
                 : "=r"(r[0]), "=r"(r[1]), "=r"(r[2]), "=r"(r[3]) : "r"(a));
}
__device__ __forceinline__ void mma16816(float (&d)[4], const uint32_t (&a)[4], uint32_t b0, uint32_t b1) {
    asm volatile("mma.sync.aligned.m16n8k16.row.col.f32.bf16.bf16.f32 {%0,%1,%2,%3}, {%4,%5,%6,%7}, {%8,%9}, {%0,%1,%2,%3};"
                 : "+f"(d[0]), "+f"(d[1]), "+f"(d[2]), "+f"(d[3]) : "r"(a[0]), "r"(a[1]), "r"(a[2]), "r"(a[3]), "r"(b0), "r"(b1));
}
__device__ __forceinline__ uint4 ldg128(const void* p) {
    uint4 v;
    asm volatile("ld.global.nc.v4.u32 {%0,%1,%2,%3}, [%4];" : "=r"(v.x), "=r"(v.y), "=r"(v.z), "=r"(v.w) : "l"(p));
    return v;
}
__device__ __forceinline__ uint4 lds128(uint32_t a) {
    uint4 v;
    asm volatile("ld.shared.v4.u32 {%0,%1,%2,%3}, [%4];" : "=r"(v.x), "=r"(v.y), "=r"(v.z), "=r"(v.w) : "r"(a));
    return v;
}

__device__ __forceinline__ void word_st(unsigned* p, float v, unsigned tag) {
    asm volatile("st.relaxed.gpu.global.u32 [%0], %1;" ::"l"(p), "r"((__float_as_uint(v) & ~3u) | tag) : "memory");
}
__device__ __forceinline__ float word_val(unsigned w) { return __uint_as_float(w & ~3u); }
struct Chunk {
    unsigned w[4];
    __device__ __forceinline__ float v(int i) const { return word_val(w[i]); }
};
__device__ __forceinline__ unsigned mail_poll(const unsigned* p) {
    unsigned r;
    asm volatile("atom.relaxed.gpu.global.or.b32 %0, [%1], 0;" : "=r"(r) : "l"(p) : "memory");
    return r;
}
template <int N, int NP = N>
__device__ __forceinline__ void mail_gather(const unsigned* const (&p)[N / NP], int stride, unsigned tag, Chunk (&r)[N]) {
#pragma unroll
    for (int i = 0; i < N; i++) {
        asm volatile("ld.relaxed.gpu.global.v4.u32 {%0,%1,%2,%3}, [%4];"
                     : "=r"(r[i].w[0]), "=r"(r[i].w[1]), "=r"(r[i].w[2]), "=r"(r[i].w[3])
                     : "l"(p[i / NP] + (i % NP) * stride) : "memory");
    }
    unsigned n = 0;
#pragma unroll 1
    while (true) {
        unsigned bad = 0;
#pragma unroll
        for (int i = 0; i < N; i++)
            bad |= (((r[i].w[0] ^ tag) | (r[i].w[1] ^ tag) | (r[i].w[2] ^ tag) | (r[i].w[3] ^ tag)) & 3u) ? 1u << i : 0u;
        bad = __reduce_or_sync(0xffffffffu, bad);
        if (bad == 0) break;
        __nanosleep(200);
#pragma unroll
        for (int i = 0; i < N; i++) {
            if (bad >> i & 1) {
#pragma unroll
                for (int e = 0; e < 4; e++) r[i].w[e] = mail_poll(p[i / NP] + (i % NP) * stride + e);
            }
        }
        if (++n > kSpinLimit) __trap();
    }
}
__device__ __forceinline__ void word_wait(const unsigned* p, unsigned tag) {
    unsigned n = 0;
    while ((mail_poll(p) ^ tag) & 3u) { __nanosleep(100); if (++n > kSpinLimit) __trap(); }
}

__device__ __forceinline__ float4 atom_add4(float4* p, float a, float b, float c, float d) {
    float4 r;
    asm volatile("atom.relaxed.gpu.global.add.v4.f32 {%0,%1,%2,%3}, [%4], {%5,%6,%7,%8};"
                 : "=f"(r.x), "=f"(r.y), "=f"(r.z), "=f"(r.w) : "l"(p), "f"(a), "f"(b), "f"(c), "f"(d) : "memory");
    return r;
}
__device__ __forceinline__ float4* acc_slot(Scratch* g, int i) { return &g->acc[(i >> 2) * 16 + (i & 3)]; }

enum { kBarCons = 1, kBarStart = 2, kBarStats = 3, kBarScalars = 4, kBarTeam = 5, kBarInit = 6 };
__device__ __forceinline__ void bar_sync(int id, int n) { asm volatile("bar.sync %0, %1;" ::"r"(id), "r"(n) : "memory"); }
__device__ __forceinline__ void bar_arrive(int id, int n) { asm volatile("bar.arrive %0, %1;" ::"r"(id), "r"(n) : "memory"); }

__device__ __forceinline__ void st_bf16(__nv_bfloat16* p, float v) {
    asm volatile("st.global.u16 [%0], %1;" ::"l"(p), "h"(__bfloat16_as_ushort(__float2bfloat16_rn(v))) : "memory");
}
__device__ __forceinline__ float fsel(bool c, float a, float b) {
    float r;
    asm("{\n.reg .pred p;\nsetp.ne.u32 p, %3, 0;\nselp.f32 %0, %1, %2, p;\n}" : "=f"(r) : "f"(a), "f"(b), "r"((unsigned)c));
    return r;
}
__device__ __forceinline__ float bf_lo(uint32_t w) { return __uint_as_float(w << 16); }
__device__ __forceinline__ float bf_hi(uint32_t w) { return __uint_as_float(w & 0xffff0000u); }
__device__ __forceinline__ float bfr(float v) { return __bfloat162float(__float2bfloat16_rn(v)); }
__device__ __forceinline__ uint32_t pack_bf16(float lo, float hi) {
    const __nv_bfloat162 v = __floats2bfloat162_rn(lo, hi);
    return *reinterpret_cast<const uint32_t*>(&v);
}
__device__ __forceinline__ float dot8(const float4& qa, const float4& qb, const uint4& v) {
    float a = qa.x * bf_lo(v.x), b = qa.y * bf_hi(v.x);
    a = fmaf(qa.z, bf_lo(v.y), a); b = fmaf(qa.w, bf_hi(v.y), b);
    a = fmaf(qb.x, bf_lo(v.z), a); b = fmaf(qb.y, bf_hi(v.z), b);
    a = fmaf(qb.z, bf_lo(v.w), a); b = fmaf(qb.w, bf_hi(v.w), b);
    return a + b;
}
__device__ __forceinline__ bool elect_one() {
    uint32_t ok;
    asm volatile("{\n.reg .pred p;\nelect.sync _|p, 0xffffffff;\nselp.u32 %0, 1, 0, p;\n}" : "=r"(ok));
    return ok != 0;
}

__host__ __device__ constexpr uint32_t tile_bytes(int t) {
    return (t == kTQ + 2 || t == kTF + 1) ? 32 * kRowB
         : t == kTF ? 48 * kRowB
         : t == kTD ? kFC * kOutRowB / 2
         : t >= kTO ? 32 * kOutRowB / 2 : kTileB;
}
constexpr uint64_t pack_back(int first) {
    uint64_t r = 0;
    for (int t = first; t < first + 21 && t < kNumTiles; t++) {
        uint32_t sum = 0;
        int j = t;
        for (; j >= 0; j--) { sum += tile_bytes(j); if (sum > kWindow) break; }
        r |= (uint64_t)(t - j > 5 ? 5 : t - j) << (3 * (t - first));
    }
    return r;
}
constexpr uint64_t kBackA = pack_back(0), kBackB = pack_back(21);
__device__ __forceinline__ int look_back(int t) {
    return (int)(((t < 21 ? kBackA : kBackB) >> (3 * (t < 21 ? t : t - 21))) & 7);
}

struct Params {
    const __nv_bfloat16* x;
    const unsigned char* k;
    const __nv_bfloat16* gate_w;
    __nv_bfloat16* out;
    Scratch* g;
    CUtensorMap tq;
    CUtensorMap tg;
    CUtensorMap tu;
    CUtensorMap tv;
    CUtensorMap td;
    CUtensorMap to;
};

__global__ void __launch_bounds__(kThreads, 1) fused_decode_kernel(const __grid_constant__ Params p) {
    extern __shared__ __align__(1024) unsigned char smem_raw[];
    Smem& sm = *reinterpret_cast<Smem*>(smem_raw);
    const int tid = threadIdx.x;
    const int lane = tid & 31;
    const int warp = tid >> 5;
    const int cta = blockIdx.x;
    const int cta0 = cta & ~(kGrp - 1);
    const int hl = (cta >> 2) & (kGH - 1);
    const uint32_t ring0 = s2u(&sm.ring[0][0]);
    const uint32_t full0 = s2u(&sm.full[0]);
    const uint32_t empty0 = s2u(&sm.empty[0]);

    uint64_t pol;
    asm volatile("createpolicy.fractional.L2::evict_first.b64 %0, 1.0;" : "=l"(pol));
    if (warp == kCW && elect_one()) {
#pragma unroll
        for (int i = 0; i < kTK; i++) mbar_init(full0 + 8 * i, 1);
        asm volatile("fence.mbarrier_init.release.cluster;" ::: "memory");
#pragma unroll
        for (int i = 0; i < kTK; i++) {
            const int row = (cta & 3) * kXR + i * 64;
            mbar_expect_tx(full0 + 8 * i, tile_bytes(i));
            tma_3d(ring0 + i * kTileB, &p.tq, (cta >> 2) * 3, row, full0 + 8 * i, pol);
            if (i < 2) tma_3d(ring0 + i * kTileB + 32 * kRowB, &p.tq, (cta >> 2) * 3, row + 32, full0 + 8 * i, pol);
        }
    }
    __syncwarp();

    if (warp == kCW) {
        const bool leader = elect_one();
        bar_sync(kBarInit, 64);
        bar_arrive(kBarStart, kThreads);
        const int key0 = (cta >> 6) * kGH * kSk + (kSk - kW) + (cta & (kGrp - 1)) * kTileKeys;
        const unsigned char* src = p.k + (size_t)key0 * kRowB;
        constexpr unsigned kProgMax = (kNumTiles - kTK) * kCTAs - 1;
        unsigned prog = 0;
        constexpr int kNever = 1 << 30;
        int mile0 = (kTV - 1 - kTK) * kCTAs + kMile, mile1 = (kTV + hl - kTK) * kCTAs + (hl < kGH - kLate ? kMile : kMileLate);
#pragma unroll 1
        for (int t = kTK; t < kNumTiles; t++) {
            const uint32_t st = t % kStages;
            const uint32_t dst = ring0 + st * kTileB, bar = full0 + 8 * st;
            if (t >= kStages) mbar_wait(empty0 + 8 * st, ((t / kStages) - 1) & 1);
            if (leader) mbar_expect_tx(bar, tile_bytes(t));
            int need = t - look_back(t);
            if (t >= kBalStart) {
                const int gp = (int)__shfl_sync(0xffffffffu, prog, 0);
                const int lead = (t - kTK) * kCTAs - gp;
                need += (lead > kLead2) - (lead <= kLead1) - (lead <= kLead0);
                const int seen = t == kNumTiles - 1 ? kNever - 1 : gp;
                if (seen >= mile0) { mile0 = kNever; if (leader) mbar_arrive(s2u(&sm.go[0])); }
                if (seen >= mile1) { mile1 = kNever; if (leader) mbar_arrive(s2u(&sm.go[1])); }
            }
            if (need >= 0) mbar_wait(full0 + 8 * (need % kStages), (need / kStages) & 1);
            if (leader) {
                if (t < kTF) {
                    bulk_g2s(dst, src, kTileB, bar, pol);
                } else if (t < kTV) {
                    const CUtensorMap* m = cta < 64 ? &p.tg : &p.tu;
                    const int row = (cta & 7) * kFR + (t - kTF) * 48, blk = ((cta >> 3) & 7) * 3;
                    tma_3d(dst, m, blk, row, bar, pol);
                    tma_3d(dst + 16 * kRowB, m, blk, row + 16, bar, pol);
                    if (t == kTF) tma_3d(dst + 32 * kRowB, m, blk, row + 32, bar, pol);
                } else if (t < kTD) {
                    tma_3d(dst, &p.tv, 0, key0 + (t - kTV) * kSk, bar, pol);
                } else {
                    tma_3d(dst, t == kTD ? &p.td : &p.to, t == kTD ? (cta >> 1) * kFC : (cta >> 1) * kOC + (t - kTO) * 32,
                           (cta & 1) * 5, bar, pol);
                }
            }
            src += (size_t)kSk * kRowB;
            if (lane == 0) {
                if (t + 1 >= kBalStart)
                    asm volatile("atom.relaxed.gpu.global.inc.u32 %0, [%1], %2;" : "=r"(prog) : "l"(&p.g->prog), "n"(kProgMax) : "memory");
                else
                    asm volatile("red.relaxed.gpu.global.inc.u32 [%0], %1;" ::"l"(&p.g->prog), "n"(kProgMax) : "memory");
            }
        }
        if (lane == 0 && prog == kProgMax) p.g->epoch = sm.tag;
        return;
    }

    unsigned tag;
    if (warp == kCW + 1) {
        if (elect_one()) {
#pragma unroll
            for (int i = 0; i < kStages; i++) { if (i >= kTK) mbar_init(full0 + 8 * i, 1); mbar_init(empty0 + 8 * i, kCW); }
            mbar_init(s2u(&sm.coef_ready), 2);
            mbar_init(s2u(&sm.go[0]), 1);
            mbar_init(s2u(&sm.go[1]), 1);
            asm volatile("fence.mbarrier_init.release.cluster;" ::: "memory");
        }
        __syncwarp();
        bar_arrive(kBarInit, 64);
        unsigned e = 0;
        if (lane == 31) asm volatile("ld.relaxed.gpu.global.u32 %0, [%1];" : "=r"(e) : "l"(&p.g->epoch) : "memory");
        if (lane < 30) {
            const uint4 v = ldg128(p.x + (lane < 20 ? (cta & 3) * kXR + lane * 8 : (cta & 7) * kFR + (lane - 20) * 8));
            *reinterpret_cast<uint4*>(&sm.rowc[kCbQ + lane * 8]) = v;
        }
        tag = __shfl_sync(0xffffffffu, e, 31) % 3u + 1u;
        if (lane == 0) sm.tag = tag;
        bar_arrive(kBarStart, kThreads);
        __nanosleep(3000);
        if (cta == 0) {
            for (int i = lane; i < kAccSlots; i += 32) *acc_slot(p.g, i) = make_float4(0.f, 0.f, 0.f, 0.f);
            __threadfence();
            __syncwarp();
            if (lane == 0) { __threadfence(); word_st(&p.g->accflag, 0.f, tag); }
        }
        {
            float z = 0.f;
#pragma unroll 1
            for (int j = lane; j < kD / 8; j += 32) {
                const uint4 gx = ldg128(p.x + j * 8), gw = ldg128(p.gate_w + j * 8);
                z += bfr(bf_lo(gx.x) * bf_lo(gw.x)) + bfr(bf_hi(gx.x) * bf_hi(gw.x));
                z += bfr(bf_lo(gx.y) * bf_lo(gw.y)) + bfr(bf_hi(gx.y) * bf_hi(gw.y));
                z += bfr(bf_lo(gx.z) * bf_lo(gw.z)) + bfr(bf_hi(gx.z) * bf_hi(gw.z));
                z += bfr(bf_lo(gx.w) * bf_lo(gw.w)) + bfr(bf_hi(gx.w) * bf_hi(gw.w));
            }
#pragma unroll
            for (int o = 16; o > 0; o >>= 1) z += __shfl_xor_sync(0xffffffffu, z, o);
            const float gate = bfr(1.0f / (1.0f + __expf(-bfr(z))));
            if (lane == 0) { sm.gate[0] = gate; sm.gate[1] = bfr(1.0f - gate); }
            if (lane < 8) sm.coef[kOC + kFC + lane] = __float2bfloat16_rn(0.f);
        }
        __nanosleep(2000);
        if (lane == 0) {
            word_wait(&p.g->accflag, tag);
            __threadfence();
        }
        __syncwarp();
        bar_sync(kBarStats, 288);
        word_st(&p.g->stat[cta][lane], sm.stat[lane], tag);
        mbar_wait(s2u(&sm.go[0]), 0);
        {
            const int mtx = lane >> 4, rb = (lane >> 1) & 7, half = lane & 1;
            const unsigned* sa = p.g->stat[cta0 + lane];
            const unsigned* sb = p.g->stat[cta0 + 32 + lane];
            const unsigned* fm = &p.g->fmail[(mtx * 8 + (cta >> 4)) * 8 + rb][((cta >> 1) & 7) * kFC + half * 12];
            const unsigned* const ps[9] = {sa + (hl >> 1) * 4, sb + (hl >> 1) * 4, sa + 24, sb + 24, sa + 28, sb + 28, fm, fm + 4, fm + 8};
            Chunk r[9];
            mail_gather<9, 1>(ps, 0, tag, r);
#pragma unroll 1
            for (int i = -1; i < kLate; i++) {
                const int hd = i < 0 ? hl : kGH - kLate + i;
                const Chunk a = i < 0 ? r[0] : hd < 14 ? r[2] : r[4], b = i < 0 ? r[1] : hd < 14 ? r[3] : r[5];
                const float m0 = hd & 1 ? a.v(2) : a.v(0), l0 = hd & 1 ? a.v(3) : a.v(1);
                const float m1 = hd & 1 ? b.v(2) : b.v(0), l1 = hd & 1 ? b.v(3) : b.v(1);
                float M = fmaxf(m0, m1);
#pragma unroll
                for (int o = 16; o > 0; o >>= 1) M = fmaxf(M, __shfl_xor_sync(0xffffffffu, M, o));
                const float w0 = __expf(m0 - M), w1 = __expf(m1 - M);
                float L = w0 * l0 + w1 * l1;
#pragma unroll
                for (int o = 16; o > 0; o >>= 1) L += __shfl_xor_sync(0xffffffffu, L, o);
                if (i < 0) { sm.wgt[lane] = w0 / L; sm.wgt[lane + 32] = w1 / L; }
                else if (lane == (cta & 31)) sm.lscale[i] = ((cta & 32) ? w1 : w0) / L;
            }
#pragma unroll
            for (int j = 0; j < 12; j++) {
                float v = r[6 + (j >> 2)].v(j & 3);
                v += __shfl_xor_sync(0xffffffffu, v, 2);
                v += __shfl_xor_sync(0xffffffffu, v, 4);
                v += __shfl_xor_sync(0xffffffffu, v, 8);
                const float gt = bfr(v);
                const float up = __shfl_xor_sync(0xffffffffu, gt, 16);
                if (lane < 2) sm.coef[kOC + half * 12 + j] = __float2bfloat16_rn((gt > 0.f ? gt : gt * 0.f) * up);
            }
        }
        bar_arrive(kBarScalars, 224);
    } else {
        bar_sync(kBarStart, kThreads);
        tag = sm.tag;

        const int mg = lane >> 2, tq = lane & 3;
        const int lk = (lane & 7) + ((lane >> 4) << 3);
        uint32_t voff[2];
#pragma unroll
        for (int i = 0; i < 2; i++) {
            const int line = lk * 3 + (warp >> 1);
            voff[i] = line * 128 + (((((warp & 1) * 4 + 2 * i + ((lane >> 3) & 1)) ^ line) & 7) << 4);
        }
#pragma unroll 1
        for (int pass = 0; pass < 3; pass++) {
            if (warp < 6) {
                const int t0 = pass == 0 ? kTQ : (pass == 1 ? kTF : kTV);
                const int t1 = pass == 0 ? kTK : (pass == 1 ? kTV : kTD);
                const uint32_t* cf = reinterpret_cast<const uint32_t*>(&sm.rowc[pass == 0 ? kCbQ : (pass == 1 ? kCbF : 0)]) + tq;
                float d[4][4];
#pragma unroll
                for (int i = 0; i < 4; i++) d[i][0] = d[i][1] = d[i][2] = d[i][3] = 0.f;
#pragma unroll 1
                for (int t = t0; t < t1; t++) {
                    const uint32_t st = t % kStages;
                    const int nk = tile_bytes(t) / (16 * kRowB);
                    if (t == kTD - kLate) bar_sync(kBarScalars, 224);
                    uint32_t b[8];
#pragma unroll
                    for (int j = 0; j < 8; j++) b[j] = cf[j * 4];
                    cf += nk * 8;
                    const bool late = t >= kTD - kLate;
                    const float ls = sm.lscale[late ? t - (kTD - kLate) : 0];
                    void* dst = late ? (void*)acc_slot(p.g, kSlots + ((cta >> 6) * kLate + t - (kTD - kLate)) * kOSlots + warp * 16 + mg * 2 + (tq >> 1))
                                     : (void*)((t < kTK ? p.g->qmail[cta] : t < kTV ? p.g->fmail[cta] : p.g->omail[t - kTV][cta]) + warp * 32 + tq * 8 + mg);
                    mbar_wait(full0 + 8 * st, (t / kStages) & 1);
                    const uint32_t a = ring0 + st * kTileB;
                    uint32_t w[8][4];
#pragma unroll
                    for (int j = 0; j < 4; j++) ldsm4t(w[j], a + voff[j & 1] + (j >> 1) * (16 * kRowB));
                    if (nk > 2) {
                        ldsm4t(w[4], a + voff[0] + 2 * (16 * kRowB));
                        ldsm4t(w[5], a + voff[1] + 2 * (16 * kRowB));
                    }
                    if (nk > 3) {
                        ldsm4t(w[6], a + voff[0] + 3 * (16 * kRowB));
                        ldsm4t(w[7], a + voff[1] + 3 * (16 * kRowB));
                    }
#pragma unroll
                    for (int j = 0; j < 4; j++) mma16816(d[j], w[j], b[(j >> 1) * 2], b[(j >> 1) * 2 + 1]);
                    if (nk > 2) { mma16816(d[0], w[4], b[4], b[5]); mma16816(d[1], w[5], b[4], b[5]); }
                    if (nk > 3) { mma16816(d[2], w[6], b[6], b[7]); mma16816(d[3], w[7], b[6], b[7]); }
                    if (pass == 2 || t == t1 - 1) {
                        const float c0 = fsel(tq & 2, d[1][0] + d[3][0], d[0][0] + d[2][0]);
                        const float c8 = fsel(tq & 2, d[1][2] + d[3][2], d[0][2] + d[2][2]);
                        if (!late) word_st((unsigned*)dst, fsel(tq & 1, c8, c0), tag);
                        else if (!(tq & 1))
                            asm volatile("red.relaxed.gpu.global.add.v4.f32 [%0], {%1,%2,%3,%4};"
                                         ::"l"(dst), "f"(c0 * ls), "f"(c8 * ls), "f"(0.f), "f"(1.f) : "memory");
#pragma unroll
                        for (int i = 0; i < 4; i++) d[i][0] = d[i][1] = d[i][2] = d[i][3] = 0.f;
                    }
                    __syncwarp();
                    if (lane == 0) mbar_arrive(empty0 + 8 * st, warp < 2 ? 2 : 1);
                }
            }
            if (pass == 1) bar_sync(kBarStats, 288);
            if (pass != 0) continue;

            bar_sync(kBarCons, 256);
            if (warp >= 6) {
                __nanosleep(800);
                word_wait(&p.g->qmail[cta0 + tid - 192][kDh - 1], tag);
            }
            bar_sync(kBarCons, 256);
            {
                Chunk r[12];
                const unsigned* ps_[3];
#pragma unroll
                for (int k = 0; k < 3; k++) {
                    const int id = tid + 256 * k, j = id / 48;
                    ps_[k] = &p.g->qmail[cta0 + j * 4][(id - j * 48) * 4];
                }
                const unsigned* const ps[3] = {ps_[0], ps_[1], ps_[2]};
                mail_gather<12, 4>(ps, kDh, tag, r);
#pragma unroll
                for (int k = 0; k < 3; k++) {
                    float v[4];
#pragma unroll
                    for (int e = 0; e < 4; e++) v[e] = bfr((r[k * 4].v(e) + r[k * 4 + 1].v(e)) + (r[k * 4 + 2].v(e) + r[k * 4 + 3].v(e)));
                    reinterpret_cast<float4*>(&sm.q[0][0])[tid + 256 * k] = make_float4(v[0], v[1], v[2], v[3]);
                }
            }
            bar_sync(kBarCons, 256);

            {
                const int g = lane >> 3, c = lane & 7;
                const uint32_t lane_off = (uint32_t)((warp * 8 + g) * kRowB + c * 16);
                const float scale = 0.07216878364870322f;
#pragma unroll 1
                for (int j = 0; j < kGH; j++) {
                    const int t = kTK + j;
                    const uint32_t st = t % kStages;
                    float4 q[6];
#pragma unroll
                    for (int i = 0; i < 6; i++) q[i] = *reinterpret_cast<const float4*>(&sm.q[j][(i >> 1) * 64 + c * 8 + (i & 1) * 4]);
                    mbar_wait(full0 + 8 * st, (t / kStages) & 1);
                    const uint32_t a = ring0 + st * kTileB + lane_off;
                    uint4 v[6];
#pragma unroll
                    for (int i = 0; i < 3; i++) { v[i] = lds128(a + i * 128); v[3 + i] = lds128(a + 4 * kRowB + i * 128); }
                    const float s0 = dot8(q[0], q[1], v[0]) + dot8(q[2], q[3], v[1]) + dot8(q[4], q[5], v[2]);
                    const float s1 = dot8(q[0], q[1], v[3]) + dot8(q[2], q[3], v[4]) + dot8(q[4], q[5], v[5]);
                    __syncwarp();
                    if (lane == 0) mbar_arrive(empty0 + 8 * st);
                    float mine = (c & 4) ? s1 : s0;
                    const float other = (c & 4) ? s0 : s1;
                    mine += __shfl_xor_sync(0xffffffffu, other, 4);
                    mine += __shfl_xor_sync(0xffffffffu, mine, 2);
                    mine += __shfl_xor_sync(0xffffffffu, mine, 1);
                    if ((c & 3) == 0) sm.sc[j][warp * 8 + c + g] = bfr(bfr(mine) * scale);
                }
            }
            bar_sync(kBarCons, 256);
            {
                float4 sv = *reinterpret_cast<const float4*>(&sm.sc[0][tid * 4]);
                float m = fmaxf(fmaxf(sv.x, sv.y), fmaxf(sv.z, sv.w));
#pragma unroll
                for (int o = 8; o > 0; o >>= 1) m = fmaxf(m, __shfl_xor_sync(0xffffffffu, m, o));
                sv.x = __expf(sv.x - m); sv.y = __expf(sv.y - m); sv.z = __expf(sv.z - m); sv.w = __expf(sv.w - m);
                *reinterpret_cast<uint2*>(&sm.rowc[tid * 4]) = make_uint2(pack_bf16(sv.x, sv.y), pack_bf16(sv.z, sv.w));
                float l = (sv.x + sv.y) + (sv.z + sv.w);
#pragma unroll
                for (int o = 8; o > 0; o >>= 1) l += __shfl_xor_sync(0xffffffffu, l, o);
                if ((lane & 15) == 0) { sm.stat[(tid >> 4) * 2] = m; sm.stat[(tid >> 4) * 2 + 1] = l; }
            }
        }

        if (warp < 5) {
            const uint32_t* cw = reinterpret_cast<const uint32_t*>(sm.coef);
            int tqp = tq;
            asm volatile("" : "+r"(tqp));
            const bool q0 = tqp == 0, q1 = tqp == 1;
            float4* slot = acc_slot(p.g, (((cta & 1) * 5 + warp) * 8 + mg) * 3 + tq);
            __nv_bfloat16* o = p.out + ((cta & 1) * 5 + warp) * 64 + tq * 24 + mg;
            float d[4][4];
            uint32_t off[4], w0[8][4], w1[8][4];
            float f0, f1, f2;
#pragma unroll
            for (int i = 0; i < 4; i++) off[i] = lk * 128 + ((((2 * i + ((lane >> 3) & 1)) ^ lk) & 7) << 4);
            {
                const uint32_t b0 = cw[48 + tq], b1 = cw[52 + tq], b2 = cw[56 + tq], b3 = cw[60 + tq];
                const float gb = sm.gate[1];
                const uint32_t a = ring0 + (kTD % kStages) * kTileB + warp * kFC * 128;
                mbar_wait(full0 + 8 * (kTD % kStages), (kTD / kStages) & 1);
#pragma unroll
                for (int i = 0; i < 4; i++) {
                    ldsm4t(w0[i], a + off[i]);
                    ldsm4t(w0[4 + i], a + off[i] + (lane < 16 ? 16 : 8) * 128);
                }
#pragma unroll
                for (int i = 0; i < 4; i++) {
                    d[i][0] = d[i][1] = d[i][2] = d[i][3] = 0.f;
                    mma16816(d[i], w0[i], b0, b1);
                    mma16816(d[i], w0[4 + i], b2, b3);
                }
                f0 = gb * fsel(q0, d[0][0], fsel(q1, d[1][2], d[3][0]));
                f1 = gb * fsel(q0, d[0][2], fsel(q1, d[2][0], d[3][2]));
                f2 = gb * fsel(q0, d[1][0], d[2][2]);
            }
#pragma unroll
            for (int i = 0; i < 4; i++) off[i] += ring0 + warp * 32 * 128;
            asm volatile("" : "+r"(off[0]), "+r"(off[1]), "+r"(off[2]), "+r"(off[3]));
            mbar_wait(full0 + 8 * (kTO % kStages), (kTO / kStages) & 1);
#pragma unroll
            for (int i = 0; i < 8; i++) ldsm4t(w0[i], off[i & 3] + (kTO % kStages) * kTileB + (i >> 2) * 2048);
            uint32_t b[12];
            float ga = sm.gate[0];
#pragma unroll
            for (int i = 0; i < 4; i++) d[i][0] = d[i][1] = d[i][2] = d[i][3] = 0.f;
            const bool early = __all_sync(0xffffffffu, mbar_test(s2u(&sm.coef_ready), 0));
            if (early) {
#pragma unroll
                for (int j = 0; j < 12; j++) b[j] = cw[j * 4 + tq];
#pragma unroll
                for (int i = 0; i < 8; i++) mma16816(d[i & 3], w0[i], b[(i >> 2) * 2], b[(i >> 2) * 2 + 1]);
            }
            asm volatile("" : "+l"(slot), "+l"(o), "+f"(ga), "+f"(f0), "+f"(f1), "+f"(f2));
            mbar_wait(full0 + 8 * ((kTO + 1) % kStages), ((kTO + 1) / kStages) & 1);
#pragma unroll
            for (int i = 0; i < 8; i++) ldsm4t(w1[i], off[i & 3] + ((kTO + 1) % kStages) * kTileB + (i >> 2) * 2048);
            if (!early) {
                mbar_wait(s2u(&sm.coef_ready), 0);
#pragma unroll
                for (int j = 0; j < 12; j++) b[j] = cw[j * 4 + tq];
#pragma unroll
                for (int i = 0; i < 8; i++) mma16816(d[i & 3], w0[i], b[(i >> 2) * 2], b[(i >> 2) * 2 + 1]);
            }
#pragma unroll
            for (int i = 0; i < 8; i++) mma16816(d[i & 3], w1[i], b[4 + (i >> 2) * 2], b[5 + (i >> 2) * 2]);
            mbar_wait(full0 + 8 * ((kTO + 2) % kStages), ((kTO + 2) / kStages) & 1);
#pragma unroll
            for (int i = 0; i < 8; i++) ldsm4t(w0[i], off[i & 3] + ((kTO + 2) % kStages) * kTileB + (i >> 2) * 2048);
#pragma unroll
            for (int i = 0; i < 8; i++) mma16816(d[i & 3], w0[i], b[8 + (i >> 2) * 2], b[9 + (i >> 2) * 2]);
            const float v0 = fmaf(ga, fsel(q0, d[0][0], fsel(q1, d[1][2], d[3][0])), f0);
            const float v1 = fmaf(ga, fsel(q0, d[0][2], fsel(q1, d[2][0], d[3][2])), f1);
            const float v2 = fmaf(ga, fsel(q0, d[1][0], d[2][2]), f2);
            if (tqp < 3) {
                const float4 old = atom_add4(slot, v0, v1, v2, 1.0f);
                if (old.w == (float)(kCTAs / 2 - 1)) {
                    st_bf16(o, old.x + v0);
                    st_bf16(o + 8, old.y + v1);
                    if (tqp < 2) st_bf16(o + 16, old.z + v2);
                }
            }
        }
        if (warp < 6) return;
    }

    {
        const int tt = warp == kCW + 1 ? 64 + lane : tid - 192;
        const int half = (cta >> 1) & 1;
        bar_sync(kBarTeam, 96);
        mbar_wait(s2u(&sm.go[1]), 0);
        if (hl >= kGH - kLate) {
            if (tt < kOC / 2) {
                float4* slot = acc_slot(p.g, kSlots + ((cta >> 6) * kLate + hl - (kGH - kLate)) * kOSlots + half * (kOC / 2) + tt);
                float4 r;
                unsigned n = 0;
                do { r = atom_add4(slot, 0.f, 0.f, 0.f, 0.f); if (++n > kSpinLimit) __trap(); } while (r.w != (float)kGrp);
                const int d = (tt >> 4) * 32 + (tt & 1) * 16 + ((tt >> 1) & 7);
                sm.coef[d] = __float2bfloat16_rn(r.x);
                sm.coef[d + 8] = __float2bfloat16_rn(r.y);
            }
        } else {
            const int c = tt % 24, sg = tt / 24;
            const unsigned* const ps[1] = {&p.g->omail[hl][cta0 + sg][half * kOC + c * 4]};
            Chunk r[16];
            mail_gather<16>(ps, 4 * kDh, tag, r);
            float4 acc = make_float4(0.f, 0.f, 0.f, 0.f);
#pragma unroll
            for (int k = 0; k < 16; k++) {
                const float w = sm.wgt[sg + 4 * k];
                acc.x = fmaf(w, r[k].v(0), acc.x); acc.y = fmaf(w, r[k].v(1), acc.y);
                acc.z = fmaf(w, r[k].v(2), acc.z); acc.w = fmaf(w, r[k].v(3), acc.w);
            }
            *reinterpret_cast<float4*>(&sm.part[sg][c * 4]) = acc;
            bar_sync(kBarTeam, 96);
            if (tt < kOC / 2) {
                const float2 a = *reinterpret_cast<const float2*>(&sm.part[0][tt * 2]), b = *reinterpret_cast<const float2*>(&sm.part[1][tt * 2]);
                const float2 e = *reinterpret_cast<const float2*>(&sm.part[2][tt * 2]), f = *reinterpret_cast<const float2*>(&sm.part[3][tt * 2]);
                reinterpret_cast<uint32_t*>(sm.coef)[tt] = pack_bf16((a.x + b.x) + (e.x + f.x), (a.y + b.y) + (e.y + f.y));
            }
        }
        __syncwarp();
        if (tt < 64 && lane == 0) mbar_arrive(s2u(&sm.coef_ready));
    }
}

__device__ float g_fb[2 * kH * kDh + kF];
__device__ __forceinline__ float ldbf(const void* p, size_t i) { return __bfloat162float(reinterpret_cast<const __nv_bfloat16*>(p)[i]); }
__global__ void fb_proj(const void* x, const void* wq, const void* wg, const void* wu) {
    const int n = blockIdx.x * blockDim.x + threadIdx.x;
    if (n < kH * kDh) {
        float a = 0.f;
        for (int k = 0; k < kD; k++) a = fmaf(ldbf(x, k), ldbf(wq, (size_t)k * kH * kDh + n), a);
        g_fb[n] = bfr(a);
    } else if (n < kH * kDh + kF) {
        const int f = n - kH * kDh;
        float a = 0.f, b = 0.f;
        for (int k = 0; k < kD; k++) { a = fmaf(ldbf(x, k), ldbf(wg, (size_t)k * kF + f), a); b = fmaf(ldbf(x, k), ldbf(wu, (size_t)k * kF + f), b); }
        a = bfr(a);
        g_fb[2 * kH * kDh + f] = bfr((a > 0.f ? a : a * 0.f) * bfr(b));
    }
}
__global__ void fb_attn(const void* kc, const void* vc) {
    __shared__ float sc[kW], red[kDh];
    const int h = blockIdx.x, t = threadIdx.x;
    const size_t base = ((size_t)h * kSk + kSk - kW) * kDh;
    float m = -INFINITY, l = 0.f, o = 0.f;
    for (int k = t; k < kW; k += kDh) {
        float a = 0.f;
        for (int d = 0; d < kDh; d++) a = fmaf(g_fb[h * kDh + d], ldbf(kc, base + (size_t)k * kDh + d), a);
        sc[k] = bfr(bfr(a) * 0.07216878364870322f);
        m = fmaxf(m, sc[k]);
    }
    red[t] = m;
    __syncthreads();
    for (int i = 0; i < kDh; i++) m = fmaxf(m, red[i]);
    for (int k = 0; k < kW; k++) {
        const float e = __expf(sc[k] - m);
        l += e;
        o = fmaf(e, ldbf(vc, base + (size_t)k * kDh + t), o);
    }
    g_fb[kH * kDh + h * kDh + t] = bfr(o / l);
}
__global__ void fb_out(const void* x, const void* gw, const void* wo, const void* wd, __nv_bfloat16* out) {
    const int n = blockIdx.x * blockDim.x + threadIdx.x;
    float z = 0.f, a = 0.f, b = 0.f;
    for (int k = 0; k < kD; k++) z += bfr(ldbf(x, k) * ldbf(gw, k));
    const float g = bfr(1.0f / (1.0f + __expf(-bfr(z))));
    for (int k = 0; k < kH * kDh; k++) a = fmaf(g_fb[kH * kDh + k], ldbf(wo, (size_t)k * kD + n), a);
    for (int k = 0; k < kF; k++) b = fmaf(g_fb[2 * kH * kDh + k], ldbf(wd, (size_t)k * kD + n), b);
    out[n] = __float2bfloat16_rn(g * a + bfr(1.0f - g) * b);
}

typedef CUresult (*EncodeFn)(CUtensorMap*, CUtensorMapDataType, cuuint32_t, void*, const cuuint64_t*, const cuuint64_t*,
                             const cuuint32_t*, const cuuint32_t*, CUtensorMapInterleave, CUtensorMapSwizzle,
                             CUtensorMapL2promotion, CUtensorMapFloatOOBfill);

void make_map(EncodeFn fn, CUtensorMap* m, void* base, int rows, int cols, int box_rows) {
    const cuuint64_t dims[3] = {64, (cuuint64_t)(cols / 64), (cuuint64_t)rows};
    const cuuint64_t strides[2] = {128, (cuuint64_t)cols * 2};
    const cuuint32_t box[3] = {64, 3, (cuuint32_t)box_rows};
    const cuuint32_t estr[3] = {1, 1, 1};
    fn(m, CU_TENSOR_MAP_DATA_TYPE_BFLOAT16, 3, base, dims, strides, box, estr, CU_TENSOR_MAP_INTERLEAVE_NONE,
       CU_TENSOR_MAP_SWIZZLE_128B, CU_TENSOR_MAP_L2_PROMOTION_NONE, CU_TENSOR_MAP_FLOAT_OOB_FILL_NONE);
}
void make_map_out(EncodeFn fn, CUtensorMap* m, void* base, int rows, int box_rows) {
    const cuuint64_t dims[3] = {64, (cuuint64_t)rows, (cuuint64_t)(kD / 64)};
    const cuuint64_t strides[2] = {(cuuint64_t)kOutRowB, 128};
    const cuuint32_t box[3] = {64, (cuuint32_t)box_rows, 5};
    const cuuint32_t estr[3] = {1, 1, 1};
    fn(m, CU_TENSOR_MAP_DATA_TYPE_BFLOAT16, 3, base, dims, strides, box, estr, CU_TENSOR_MAP_INTERLEAVE_NONE,
       CU_TENSOR_MAP_SWIZZLE_128B, CU_TENSOR_MAP_L2_PROMOTION_NONE, CU_TENSOR_MAP_FLOAT_OOB_FILL_NONE);
}

}

extern "C" void kernel_launch(void* const* d_in, const int* in_sizes, int n_in, void* d_out, int out_size) {
    (void)in_sizes; (void)n_in; (void)out_size;
    static EncodeFn encode = nullptr;
    static void* scratch = nullptr;
    static int resident = -1;
    if (resident < 0) {
        cudaGetSymbolAddress(&scratch, g_scratch);
        void* fn = nullptr;
        cudaDriverEntryPointQueryResult qr;
        cudaGetDriverEntryPoint("cuTensorMapEncodeTiled", &fn, cudaEnableDefault, &qr);
        encode = (EncodeFn)fn;
        cudaFuncSetAttribute(fused_decode_kernel, cudaFuncAttributeMaxDynamicSharedMemorySize, (int)sizeof(Smem));
        int dev = 0, sms = 0, per_sm = 0;
        cudaGetDevice(&dev);
        cudaDeviceGetAttribute(&sms, cudaDevAttrMultiProcessorCount, dev);
        cudaOccupancyMaxActiveBlocksPerMultiprocessor(&per_sm, fused_decode_kernel, kThreads, sizeof(Smem));
        resident = sms * per_sm;
    }
    if (resident < kCTAs || !encode) {
        fb_proj<<<(kH * kDh + kF) / 128, 128, 0, cudaStreamPerThread>>>(d_in[0], d_in[3], d_in[6], d_in[7]);
        fb_attn<<<kH, kDh, 0, cudaStreamPerThread>>>(d_in[1], d_in[2]);
        fb_out<<<kD / 32, 32, 0, cudaStreamPerThread>>>(d_in[0], d_in[9], d_in[4], d_in[8], (__nv_bfloat16*)d_out);
        return;
    }
    Params p;
    p.x = (const __nv_bfloat16*)d_in[0];
    p.k = (const unsigned char*)d_in[1];
    p.gate_w = (const __nv_bfloat16*)d_in[9];
    p.out = (__nv_bfloat16*)d_out;
    p.g = (Scratch*)scratch;
    make_map(encode, &p.tq, d_in[3], kD, kH * kDh, 32);
    make_map(encode, &p.tg, d_in[6], kD, kF, 16);
    make_map(encode, &p.tu, d_in[7], kD, kF, 16);
    make_map(encode, &p.tv, d_in[2], kH * kSk, kDh, kTileKeys);
    make_map_out(encode, &p.td, d_in[8], kF, kFC);
    make_map_out(encode, &p.to, d_in[4], kH * kDh, 32);
    fused_decode_kernel<<<kCTAs, kThreads, sizeof(Smem), cudaStreamPerThread>>>(p);
}
```

```cpp
#include <cuda_runtime.h>
#include <cuda_bf16.h>
#include <cuda.h>
#include <math.h>
#include <stdint.h>

namespace {

constexpr int kD = 640;
constexpr int kH = 32;
constexpr int kDh = 192;
constexpr int kSk = 32768;
constexpr int kW = 4096;
constexpr int kF = 1536;
constexpr int kCTAs = 128;
constexpr int kGrp = 64;
constexpr int kGH = kH * kGrp / kCTAs;
constexpr int kCW = 8;
constexpr int kThreads = kCW * 32 + 64;
constexpr int kTileKeys = kW / kGrp;
constexpr int kRowB = kDh * 2;
constexpr int kTileB = kTileKeys * kRowB;
constexpr int kStages = 8;
constexpr int kOutRowB = kD * 2;
constexpr int kFC = 2 * kF / kCTAs;
constexpr int kOC = 2 * kH * kDh / kCTAs;
constexpr int kXR = kD / 4;
constexpr int kFR = kD / 8;
constexpr int kTQ = 0;
constexpr int kTK = 3;
constexpr int kTF = kTK + kGH;
constexpr int kTV = kTF + 2;
constexpr int kTD = kTV + kGH;
constexpr int kTO = kTD + 1;
constexpr int kNumTiles = kTO + 3;
constexpr int kSlots = 240;
constexpr int kLate = 4;
constexpr int kOSlots = kDh / 2;
constexpr int kAccSlots = kSlots + 2 * kLate * kOSlots;
constexpr unsigned kSpinLimit = 1u << 24;
static_assert(kTD - kLate + kStages > kNumTiles - 1, "the producer must be able to finish before the late V tiles are consumed");

constexpr uint32_t kWindow = 71000;
constexpr int kBalStart = 8;
constexpr int kLead0 = 16, kLead1 = 72, kLead2 = 128;
constexpr int kMile = 576, kMileLate = 384;

constexpr int kCbQ = kGH * kTileKeys, kCbF = kCbQ + kXR, kCbLen = kCbF + kFR;

struct Smem {
    alignas(1024) unsigned char ring[kStages][kTileB];
    alignas(16) float q[kGH][kDh];
    alignas(16) float sc[kGH][kTileKeys];
    alignas(16) __nv_bfloat16 rowc[kCbLen];
    alignas(16) __nv_bfloat16 coef[128];
    alignas(16) float part[4][kOC];
    float wgt[kGrp];
    float lscale[kLate];
    float stat[2 * kGH];
    float gate[2];
    unsigned tag;
    alignas(8) unsigned long long full[kStages];
    alignas(8) unsigned long long empty[kStages];
    alignas(8) unsigned long long coef_ready;
    alignas(8) unsigned long long go[2];
};

struct Scratch {
    alignas(256) unsigned epoch;
    alignas(256) unsigned accflag;
    alignas(256) unsigned prog;
    alignas(256) float4 acc[kAccSlots * 4];
    alignas(256) unsigned stat[kCTAs][2 * kGH];
    alignas(256) unsigned qmail[kCTAs][kDh];
    alignas(256) unsigned fmail[kCTAs][kDh];
    alignas(256) unsigned omail[kGH - kLate][kCTAs][kDh];
};
__device__ Scratch g_scratch;

__device__ __forceinline__ uint32_t s2u(const void* p) { return (uint32_t)__cvta_generic_to_shared(p); }

__device__ __forceinline__ void mbar_init(uint32_t bar, uint32_t cnt) {
    asm volatile("mbarrier.init.shared::cta.b64 [%0], %1;" ::"r"(bar), "r"(cnt) : "memory");
}
__device__ __forceinline__ void mbar_expect_tx(uint32_t bar, uint32_t bytes) {
    asm volatile("mbarrier.arrive.expect_tx.shared::cta.b64 _, [%0], %1;" ::"r"(bar), "r"(bytes) : "memory");
}
__device__ __forceinline__ void mbar_arrive(uint32_t bar, uint32_t cnt = 1) {
    asm volatile("mbarrier.arrive.shared::cta.b64 _, [%0], %1;" ::"r"(bar), "r"(cnt) : "memory");
}
__device__ __forceinline__ void mbar_wait(uint32_t bar, uint32_t parity) {
    asm volatile("{\n.reg .pred p;\n.reg .u32 n;\nmov.u32 n, 0;\n"
                 "WL:\nmbarrier.try_wait.parity.shared::cta.b64 p, [%0], %1;\n@p bra WD;\n"
                 "add.u32 n, n, 1;\nsetp.lt.u32 p, n, %2;\n@p bra WL;\ntrap;\nWD:\n}"
                 ::"r"(bar), "r"(parity), "n"(kSpinLimit) : "memory");
}
__device__ __forceinline__ bool mbar_test(uint32_t bar, uint32_t parity) {
    uint32_t ok;
    asm volatile("{\n.reg .pred p;\nmbarrier.test_wait.parity.shared::cta.b64 p, [%1], %2;\nselp.u32 %0, 1, 0, p;\n}"
                 : "=r"(ok) : "r"(bar), "r"(parity) : "memory");
    return ok != 0;
}
__device__ __forceinline__ void bulk_g2s(uint32_t dst, const void* src, uint32_t bytes, uint32_t bar, uint64_t pol) {
    asm volatile("cp.async.bulk.shared::cluster.global.mbarrier::complete_tx::bytes.L2::cache_hint [%0], [%1], %2, [%3], %4;"
                 ::"r"(dst), "l"(src), "r"(bytes), "r"(bar), "l"(pol) : "memory");
}
__device__ __forceinline__ void tma_3d(uint32_t dst, const CUtensorMap* map, int c1, int c2, uint32_t bar, uint64_t pol) {
    asm volatile("cp.async.bulk.tensor.3d.shared::cluster.global.mbarrier::complete_tx::bytes.L2::cache_hint [%0], [%1, {%4, %3, %6}], [%2], %5;"
                 ::"r"(dst), "l"(map), "r"(bar), "r"(c1), "r"(0), "l"(pol), "r"(c2) : "memory");
}
__device__ __forceinline__ void ldsm4t(uint32_t (&r)[4], uint32_t a) {
    asm volatile("ldmatrix.sync.aligned.m8n8.x4.trans.shared.b16 {%0,%1,%2,%3}, [%4];"
                 : "=r"(r[0]), "=r"(r[1]), "=r"(r[2]), "=r"(r[3]) : "r"(a));
}
__device__ __forceinline__ void mma16816(float (&d)[4], const uint32_t (&a)[4], uint32_t b0, uint32_t b1) {
    asm volatile("mma.sync.aligned.m16n8k16.row.col.f32.bf16.bf16.f32 {%0,%1,%2,%3}, {%4,%5,%6,%7}, {%8,%9}, {%0,%1,%2,%3};"
                 : "+f"(d[0]), "+f"(d[1]), "+f"(d[2]), "+f"(d[3]) : "r"(a[0]), "r"(a[1]), "r"(a[2]), "r"(a[3]), "r"(b0), "r"(b1));
}
__device__ __forceinline__ uint4 ldg128(const void* p) {
    uint4 v;
    asm volatile("ld.global.nc.v4.u32 {%0,%1,%2,%3}, [%4];" : "=r"(v.x), "=r"(v.y), "=r"(v.z), "=r"(v.w) : "l"(p));
    return v;
}
__device__ __forceinline__ uint4 lds128(uint32_t a) {
    uint4 v;
    asm volatile("ld.shared.v4.u32 {%0,%1,%2,%3}, [%4];" : "=r"(v.x), "=r"(v.y), "=r"(v.z), "=r"(v.w) : "r"(a));
    return v;
}

__device__ __forceinline__ void word_st(unsigned* p, float v, unsigned tag) {
    asm volatile("st.relaxed.gpu.global.u32 [%0], %1;" ::"l"(p), "r"((__float_as_uint(v) & ~3u) | tag) : "memory");
}
__device__ __forceinline__ float word_val(unsigned w) { return __uint_as_float(w & ~3u); }
struct Chunk {
    unsigned w[4];
    __device__ __forceinline__ float v(int i) const { return word_val(w[i]); }
};
__device__ __forceinline__ unsigned mail_poll(const unsigned* p) {
    unsigned r;
    asm volatile("atom.relaxed.gpu.global.or.b32 %0, [%1], 0;" : "=r"(r) : "l"(p) : "memory");
    return r;
}
template <int N, int NP = N>
__device__ __forceinline__ void mail_gather(const unsigned* const (&p)[N / NP], int stride, unsigned tag, Chunk (&r)[N]) {
#pragma unroll
    for (int i = 0; i < N; i++) {
        asm volatile("ld.relaxed.gpu.global.v4.u32 {%0,%1,%2,%3}, [%4];"
                     : "=r"(r[i].w[0]), "=r"(r[i].w[1]), "=r"(r[i].w[2]), "=r"(r[i].w[3])
                     : "l"(p[i / NP] + (i % NP) * stride) : "memory");
    }
    unsigned n = 0;
#pragma unroll 1
    while (true) {
        unsigned bad = 0;
#pragma unroll
        for (int i = 0; i < N; i++)
            bad |= (((r[i].w[0] ^ tag) | (r[i].w[1] ^ tag) | (r[i].w[2] ^ tag) | (r[i].w[3] ^ tag)) & 3u) ? 1u << i : 0u;
        bad = __reduce_or_sync(0xffffffffu, bad);
        if (bad == 0) break;
        __nanosleep(200);
#pragma unroll
        for (int i = 0; i < N; i++) {
            if (bad >> i & 1) {
#pragma unroll
                for (int e = 0; e < 4; e++) r[i].w[e] = mail_poll(p[i / NP] + (i % NP) * stride + e);
            }
        }
        if (++n > kSpinLimit) __trap();
    }
}
__device__ __forceinline__ void word_wait(const unsigned* p, unsigned tag) {
    unsigned n = 0;
    while ((mail_poll(p) ^ tag) & 3u) { __nanosleep(100); if (++n > kSpinLimit) __trap(); }
}

__device__ __forceinline__ float4 atom_add4(float4* p, float a, float b, float c, float d) {
    float4 r;
    asm volatile("atom.relaxed.gpu.global.add.v4.f32 {%0,%1,%2,%3}, [%4], {%5,%6,%7,%8};"
                 : "=f"(r.x), "=f"(r.y), "=f"(r.z), "=f"(r.w) : "l"(p), "f"(a), "f"(b), "f"(c), "f"(d) : "memory");
    return r;
}
__device__ __forceinline__ float4* acc_slot(Scratch* g, int i) { return &g->acc[(i >> 2) * 16 + (i & 3)]; }

enum { kBarCons = 1, kBarStart = 2, kBarStats = 3, kBarScalars = 4, kBarTeam = 5, kBarInit = 6 };
__device__ __forceinline__ void bar_sync(int id, int n) { asm volatile("bar.sync %0, %1;" ::"r"(id), "r"(n) : "memory"); }
__device__ __forceinline__ void bar_arrive(int id, int n) { asm volatile("bar.arrive %0, %1;" ::"r"(id), "r"(n) : "memory"); }

__device__ __forceinline__ void st_bf16(__nv_bfloat16* p, float v) {
    asm volatile("st.global.u16 [%0], %1;" ::"l"(p), "h"(__bfloat16_as_ushort(__float2bfloat16_rn(v))) : "memory");
}
__device__ __forceinline__ float fsel(bool c, float a, float b) {
    float r;
    asm("{\n.reg .pred p;\nsetp.ne.u32 p, %3, 0;\nselp.f32 %0, %1, %2, p;\n}" : "=f"(r) : "f"(a), "f"(b), "r"((unsigned)c));
    return r;
}
__device__ __forceinline__ float bf_lo(uint32_t w) { return __uint_as_float(w << 16); }
__device__ __forceinline__ float bf_hi(uint32_t w) { return __uint_as_float(w & 0xffff0000u); }
__device__ __forceinline__ float bfr(float v) { return __bfloat162float(__float2bfloat16_rn(v)); }
__device__ __forceinline__ uint32_t pack_bf16(float lo, float hi) {
    const __nv_bfloat162 v = __floats2bfloat162_rn(lo, hi);
    return *reinterpret_cast<const uint32_t*>(&v);
}
__device__ __forceinline__ float dot8(const float4& qa, const float4& qb, const uint4& v) {
    float a = qa.x * bf_lo(v.x), b = qa.y * bf_hi(v.x);
    a = fmaf(qa.z, bf_lo(v.y), a); b = fmaf(qa.w, bf_hi(v.y), b);
    a = fmaf(qb.x, bf_lo(v.z), a); b = fmaf(qb.y, bf_hi(v.z), b);
    a = fmaf(qb.z, bf_lo(v.w), a); b = fmaf(qb.w, bf_hi(v.w), b);
    return a + b;
}
__device__ __forceinline__ bool elect_one() {
    uint32_t ok;
    asm volatile("{\n.reg .pred p;\nelect.sync _|p, 0xffffffff;\nselp.u32 %0, 1, 0, p;\n}" : "=r"(ok));
    return ok != 0;
}

__host__ __device__ constexpr uint32_t tile_bytes(int t) {
    return (t == kTQ + 2 || t == kTF + 1) ? 32 * kRowB
         : t == kTF ? 48 * kRowB
         : t == kTD ? kFC * kOutRowB / 2
         : t >= kTO ? 32 * kOutRowB / 2 : kTileB;
}
constexpr uint64_t pack_back(int first) {
    uint64_t r = 0;
    for (int t = first; t < first + 21 && t < kNumTiles; t++) {
        uint32_t sum = 0;
        int j = t;
        for (; j >= 0; j--) { sum += tile_bytes(j); if (sum > kWindow) break; }
        r |= (uint64_t)(t - j > 5 ? 5 : t - j) << (3 * (t - first));
    }
    return r;
}
constexpr uint64_t kBackA = pack_back(0), kBackB = pack_back(21);
__device__ __forceinline__ int look_back(int t) {
    return (int)(((t < 21 ? kBackA : kBackB) >> (3 * (t < 21 ? t : t - 21))) & 7);
}

struct Params {
    const __nv_bfloat16* x;
    const unsigned char* k;
    const __nv_bfloat16* gate_w;
    __nv_bfloat16* out;
    Scratch* g;
    CUtensorMap tq;
    CUtensorMap tg;
    CUtensorMap tu;
    CUtensorMap tv;
    CUtensorMap td;
    CUtensorMap to;
};

__global__ void __launch_bounds__(kThreads, 1)
fused_decode_kernel(const unsigned char* __restrict__ wq, const __grid_constant__ Params p) {
    if (threadIdx.x == 0)
        asm volatile("cp.async.bulk.prefetch.L2.global [%0], %1;"
                     ::"l"(wq + (size_t)((blockIdx.x >> 5) * kXR + (blockIdx.x & 31)) * (kH * kRowB)), "n"(kH * kRowB) : "memory");
    extern __shared__ __align__(1024) unsigned char smem_raw[];
    Smem& sm = *reinterpret_cast<Smem*>(smem_raw);
    const int tid = threadIdx.x;
    const int lane = tid & 31;
    const int warp = tid >> 5;
    const int cta = blockIdx.x;
    const int cta0 = cta & ~(kGrp - 1);
    const int hl = (cta >> 2) & (kGH - 1);
    const uint32_t ring0 = s2u(&sm.ring[0][0]);
    const uint32_t full0 = s2u(&sm.full[0]);
    const uint32_t empty0 = s2u(&sm.empty[0]);

    uint64_t pol;
    asm volatile("createpolicy.fractional.L2::evict_first.b64 %0, 1.0;" : "=l"(pol));
    if (warp == kCW && elect_one()) {
#pragma unroll
        for (int i = 0; i < kTK; i++) mbar_init(full0 + 8 * i, 1);
        asm volatile("fence.mbarrier_init.release.cluster;" ::: "memory");
#pragma unroll
        for (int i = 0; i < kTK; i++) {
            const int row = (cta & 3) * kXR + i * 64;
            mbar_expect_tx(full0 + 8 * i, tile_bytes(i));
            tma_3d(ring0 + i * kTileB, &p.tq, (cta >> 2) * 3, row, full0 + 8 * i, pol);
            if (i < 2) tma_3d(ring0 + i * kTileB + 32 * kRowB, &p.tq, (cta >> 2) * 3, row + 32, full0 + 8 * i, pol);
        }
    }
    __syncwarp();

    if (warp == kCW) {
        const bool leader = elect_one();
        bar_sync(kBarInit, 64);
        bar_arrive(kBarStart, kThreads);
        const int key0 = (cta >> 6) * kGH * kSk + (kSk - kW) + (cta & (kGrp - 1)) * kTileKeys;
        const unsigned char* src = p.k + (size_t)key0 * kRowB;
        constexpr unsigned kProgMax = (kNumTiles - kTK) * kCTAs - 1;
        unsigned prog = 0;
        constexpr int kNever = 1 << 30;
        int mile0 = (kTV - 1 - kTK) * kCTAs + kMile, mile1 = (kTV + hl - kTK) * kCTAs + (hl < kGH - kLate ? kMile : kMileLate);
#pragma unroll 1
        for (int t = kTK; t < kNumTiles; t++) {
            const uint32_t st = t % kStages;
            const uint32_t dst = ring0 + st * kTileB, bar = full0 + 8 * st;
            if (t >= kStages) mbar_wait(empty0 + 8 * st, ((t / kStages) - 1) & 1);
            if (leader) mbar_expect_tx(bar, tile_bytes(t));
            int need = t - look_back(t);
            if (t >= kBalStart) {
                const int gp = (int)__shfl_sync(0xffffffffu, prog, 0);
                const int lead = (t - kTK) * kCTAs - gp;
                need += (lead > kLead2) - (lead <= kLead1) - (lead <= kLead0);
                const int seen = t == kNumTiles - 1 ? kNever - 1 : gp;
                if (seen >= mile0) { mile0 = kNever; if (leader) mbar_arrive(s2u(&sm.go[0])); }
                if (seen >= mile1) { mile1 = kNever; if (leader) mbar_arrive(s2u(&sm.go[1])); }
            }
            if (need >= 0) mbar_wait(full0 + 8 * (need % kStages), (need / kStages) & 1);
            if (leader) {
                if (t < kTF) {
                    bulk_g2s(dst, src, kTileB, bar, pol);
                } else if (t < kTV) {
                    const CUtensorMap* m = cta < 64 ? &p.tg : &p.tu;
                    const int row = (cta & 7) * kFR + (t - kTF) * 48, blk = ((cta >> 3) & 7) * 3;
                    tma_3d(dst, m, blk, row, bar, pol);
                    tma_3d(dst + 16 * kRowB, m, blk, row + 16, bar, pol);
                    if (t == kTF) tma_3d(dst + 32 * kRowB, m, blk, row + 32, bar, pol);
                } else if (t < kTD) {
                    tma_3d(dst, &p.tv, 0, key0 + (t - kTV) * kSk, bar, pol);
                } else {
                    tma_3d(dst, t == kTD ? &p.td : &p.to, t == kTD ? (cta >> 1) * kFC : (cta >> 1) * kOC + (t - kTO) * 32,
                           (cta & 1) * 5, bar, pol);
                }
            }
            if (leader && t == 12) {
                asm volatile("prefetch.tensormap [%0];" ::"l"(cta < 64 ? &p.tg : &p.tu) : "memory");
                asm volatile("prefetch.tensormap [%0];" ::"l"(&p.tv) : "memory");
                asm volatile("prefetch.tensormap [%0];" ::"l"(&p.td) : "memory");
                asm volatile("prefetch.tensormap [%0];" ::"l"(&p.to) : "memory");
            }
            src += (size_t)kSk * kRowB;
            if (lane == 0) {
                if (t + 1 >= kBalStart)
                    asm volatile("atom.relaxed.gpu.global.inc.u32 %0, [%1], %2;" : "=r"(prog) : "l"(&p.g->prog), "n"(kProgMax) : "memory");
                else
                    asm volatile("red.relaxed.gpu.global.inc.u32 [%0], %1;" ::"l"(&p.g->prog), "n"(kProgMax) : "memory");
            }
        }
        if (lane == 0 && prog == kProgMax) p.g->epoch = sm.tag;
        return;
    }

    unsigned tag;
    if (warp == kCW + 1) {
        if (elect_one()) {
#pragma unroll
            for (int i = 0; i < kStages; i++) { if (i >= kTK) mbar_init(full0 + 8 * i, 1); mbar_init(empty0 + 8 * i, kCW); }
            mbar_init(s2u(&sm.coef_ready), 2);
            mbar_init(s2u(&sm.go[0]), 1);
            mbar_init(s2u(&sm.go[1]), 1);
            asm volatile("fence.mbarrier_init.release.cluster;" ::: "memory");
        }
        __syncwarp();
        bar_arrive(kBarInit, 64);
        unsigned e = 0;
        if (lane == 31) asm volatile("ld.relaxed.gpu.global.u32 %0, [%1];" : "=r"(e) : "l"(&p.g->epoch) : "memory");
        if (lane < 30) {
            const uint4 v = ldg128(p.x + (lane < 20 ? (cta & 3) * kXR + lane * 8 : (cta & 7) * kFR + (lane - 20) * 8));
            *reinterpret_cast<uint4*>(&sm.rowc[kCbQ + lane * 8]) = v;
        }
        tag = __shfl_sync(0xffffffffu, e, 31) % 3u + 1u;
        if (lane == 0) sm.tag = tag;
        bar_arrive(kBarStart, kThreads);
        __nanosleep(3000);
        if (cta == 0) {
            for (int i = lane; i < kAccSlots; i += 32) *acc_slot(p.g, i) = make_float4(0.f, 0.f, 0.f, 0.f);
            __threadfence();
            __syncwarp();
            if (lane == 0) { __threadfence(); word_st(&p.g->accflag, 0.f, tag); }
        }
        {
            float z = 0.f;
#pragma unroll 1
            for (int j = lane; j < kD / 8; j += 32) {
                const uint4 gx = ldg128(p.x + j * 8), gw = ldg128(p.gate_w + j * 8);
                z += bfr(bf_lo(gx.x) * bf_lo(gw.x)) + bfr(bf_hi(gx.x) * bf_hi(gw.x));
                z += bfr(bf_lo(gx.y) * bf_lo(gw.y)) + bfr(bf_hi(gx.y) * bf_hi(gw.y));
                z += bfr(bf_lo(gx.z) * bf_lo(gw.z)) + bfr(bf_hi(gx.z) * bf_hi(gw.z));
                z += bfr(bf_lo(gx.w) * bf_lo(gw.w)) + bfr(bf_hi(gx.w) * bf_hi(gw.w));
            }
#pragma unroll
            for (int o = 16; o > 0; o >>= 1) z += __shfl_xor_sync(0xffffffffu, z, o);
            const float gate = bfr(1.0f / (1.0f + __expf(-bfr(z))));
            if (lane == 0) { sm.gate[0] = gate; sm.gate[1] = bfr(1.0f - gate); }
            if (lane < 8) sm.coef[kOC + kFC + lane] = __float2bfloat16_rn(0.f);
        }
        __nanosleep(2000);
        if (lane == 0) {
            word_wait(&p.g->accflag, tag);
            __threadfence();
        }
        __syncwarp();
        bar_sync(kBarStats, 288);
        word_st(&p.g->stat[cta][lane], sm.stat[lane], tag);
        mbar_wait(s2u(&sm.go[0]), 0);
        {
            const int mtx = lane >> 4, rb = (lane >> 1) & 7, half = lane & 1;
            const unsigned* sa = p.g->stat[cta0 + lane];
            const unsigned* sb = p.g->stat[cta0 + 32 + lane];
            const unsigned* fm = &p.g->fmail[(mtx * 8 + (cta >> 4)) * 8 + rb][((cta >> 1) & 7) * kFC + half * 12];
            const unsigned* const ps[9] = {sa + (hl >> 1) * 4, sb + (hl >> 1) * 4, sa + 24, sb + 24, sa + 28, sb + 28, fm, fm + 4, fm + 8};
            Chunk r[9];
            mail_gather<9, 1>(ps, 0, tag, r);
#pragma unroll 1
            for (int i = -1; i < kLate; i++) {
                const int hd = i < 0 ? hl : kGH - kLate + i;
                const Chunk a = i < 0 ? r[0] : hd < 14 ? r[2] : r[4], b = i < 0 ? r[1] : hd < 14 ? r[3] : r[5];
                const float m0 = hd & 1 ? a.v(2) : a.v(0), l0 = hd & 1 ? a.v(3) : a.v(1);
                const float m1 = hd & 1 ? b.v(2) : b.v(0), l1 = hd & 1 ? b.v(3) : b.v(1);
                float M = fmaxf(m0, m1);
#pragma unroll
                for (int o = 16; o > 0; o >>= 1) M = fmaxf(M, __shfl_xor_sync(0xffffffffu, M, o));
                const float w0 = __expf(m0 - M), w1 = __expf(m1 - M);
                float L = w0 * l0 + w1 * l1;
#pragma unroll
                for (int o = 16; o > 0; o >>= 1) L += __shfl_xor_sync(0xffffffffu, L, o);
                if (i < 0) { sm.wgt[lane] = w0 / L; sm.wgt[lane + 32] = w1 / L; }
                else if (lane == (cta & 31)) sm.lscale[i] = ((cta & 32) ? w1 : w0) / L;
            }
#pragma unroll
            for (int j = 0; j < 12; j++) {
                float v = r[6 + (j >> 2)].v(j & 3);
                v += __shfl_xor_sync(0xffffffffu, v, 2);
                v += __shfl_xor_sync(0xffffffffu, v, 4);
                v += __shfl_xor_sync(0xffffffffu, v, 8);
                const float gt = bfr(v);
                const float up = __shfl_xor_sync(0xffffffffu, gt, 16);
                if (lane < 2) sm.coef[kOC + half * 12 + j] = __float2bfloat16_rn((gt > 0.f ? gt : gt * 0.f) * up);
            }
        }
        bar_arrive(kBarScalars, 224);
    } else {
        bar_sync(kBarStart, kThreads);
        tag = sm.tag;

        const int mg = lane >> 2, tq = lane & 3;
        const int lk = (lane & 7) + ((lane >> 4) << 3);
        uint32_t voff[2];
#pragma unroll
        for (int i = 0; i < 2; i++) {
            const int line = lk * 3 + (warp >> 1);
            voff[i] = line * 128 + (((((warp & 1) * 4 + 2 * i + ((lane >> 3) & 1)) ^ line) & 7) << 4);
        }
#pragma unroll 1
        for (int pass = 0; pass < 3; pass++) {
            if (warp < 6) {
                const int t0 = pass == 0 ? kTQ : (pass == 1 ? kTF : kTV);
                const int t1 = pass == 0 ? kTK : (pass == 1 ? kTV : kTD);
                const uint32_t* cf = reinterpret_cast<const uint32_t*>(&sm.rowc[pass == 0 ? kCbQ : (pass == 1 ? kCbF : 0)]) + tq;
                float d[4][4];
#pragma unroll
                for (int i = 0; i < 4; i++) d[i][0] = d[i][1] = d[i][2] = d[i][3] = 0.f;
#pragma unroll 1
                for (int t = t0; t < t1; t++) {
                    const uint32_t st = t % kStages;
                    const int nk = tile_bytes(t) / (16 * kRowB);
                    if (t == kTD - kLate) bar_sync(kBarScalars, 224);
                    uint32_t b[8];
#pragma unroll
                    for (int j = 0; j < 8; j++) b[j] = cf[j * 4];
                    cf += nk * 8;
                    const bool late = t >= kTD - kLate;
                    const float ls = sm.lscale[late ? t - (kTD - kLate) : 0];
                    void* dst = late ? (void*)acc_slot(p.g, kSlots + ((cta >> 6) * kLate + t - (kTD - kLate)) * kOSlots + warp * 16 + mg * 2 + (tq >> 1))
                                     : (void*)((t < kTK ? p.g->qmail[cta] : t < kTV ? p.g->fmail[cta] : p.g->omail[t - kTV][cta]) + warp * 32 + tq * 8 + mg);
                    mbar_wait(full0 + 8 * st, (t / kStages) & 1);
                    const uint32_t a = ring0 + st * kTileB;
                    uint32_t w[8][4];
#pragma unroll
                    for (int j = 0; j < 4; j++) ldsm4t(w[j], a + voff[j & 1] + (j >> 1) * (16 * kRowB));
                    if (nk > 2) {
                        ldsm4t(w[4], a + voff[0] + 2 * (16 * kRowB));
                        ldsm4t(w[5], a + voff[1] + 2 * (16 * kRowB));
                    }
                    if (nk > 3) {
                        ldsm4t(w[6], a + voff[0] + 3 * (16 * kRowB));
                        ldsm4t(w[7], a + voff[1] + 3 * (16 * kRowB));
                    }
#pragma unroll
                    for (int j = 0; j < 4; j++) mma16816(d[j], w[j], b[(j >> 1) * 2], b[(j >> 1) * 2 + 1]);
                    if (nk > 2) { mma16816(d[0], w[4], b[4], b[5]); mma16816(d[1], w[5], b[4], b[5]); }
                    if (nk > 3) { mma16816(d[2], w[6], b[6], b[7]); mma16816(d[3], w[7], b[6], b[7]); }
                    if (pass == 2 || t == t1 - 1) {
                        const float c0 = fsel(tq & 2, d[1][0] + d[3][0], d[0][0] + d[2][0]);
                        const float c8 = fsel(tq & 2, d[1][2] + d[3][2], d[0][2] + d[2][2]);
                        if (!late) word_st((unsigned*)dst, fsel(tq & 1, c8, c0), tag);
                        else if (!(tq & 1))
                            asm volatile("red.relaxed.gpu.global.add.v4.f32 [%0], {%1,%2,%3,%4};"
                                         ::"l"(dst), "f"(c0 * ls), "f"(c8 * ls), "f"(0.f), "f"(1.f) : "memory");
#pragma unroll
                        for (int i = 0; i < 4; i++) d[i][0] = d[i][1] = d[i][2] = d[i][3] = 0.f;
                    }
                    __syncwarp();
                    if (lane == 0) mbar_arrive(empty0 + 8 * st, warp < 2 ? 2 : 1);
                }
            }
            if (pass == 1) bar_sync(kBarStats, 288);
            if (pass != 0) continue;

            bar_sync(kBarCons, 256);
            if (warp >= 6) {
                __nanosleep(800);
                word_wait(&p.g->qmail[cta0 + tid - 192][kDh - 1], tag);
            }
            bar_sync(kBarCons, 256);
            {
                Chunk r[12];
                const unsigned* ps_[3];
#pragma unroll
                for (int k = 0; k < 3; k++) {
                    const int id = tid + 256 * k, j = id / 48;
                    ps_[k] = &p.g->qmail[cta0 + j * 4][(id - j * 48) * 4];
                }
                const unsigned* const ps[3] = {ps_[0], ps_[1], ps_[2]};
                mail_gather<12, 4>(ps, kDh, tag, r);
#pragma unroll
                for (int k = 0; k < 3; k++) {
                    float v[4];
#pragma unroll
                    for (int e = 0; e < 4; e++) v[e] = bfr((r[k * 4].v(e) + r[k * 4 + 1].v(e)) + (r[k * 4 + 2].v(e) + r[k * 4 + 3].v(e)));
                    reinterpret_cast<float4*>(&sm.q[0][0])[tid + 256 * k] = make_float4(v[0], v[1], v[2], v[3]);
                }
            }
            bar_sync(kBarCons, 256);

            {
                const int g = lane >> 3, c = lane & 7;
                const uint32_t lane_off = (uint32_t)((warp * 8 + g) * kRowB + c * 16);
                const float scale = 0.07216878364870322f;
#pragma unroll 1
                for (int j = 0; j < kGH; j++) {
                    const int t = kTK + j;
                    const uint32_t st = t % kStages;
                    float4 q[6];
#pragma unroll
                    for (int i = 0; i < 6; i++) q[i] = *reinterpret_cast<const float4*>(&sm.q[j][(i >> 1) * 64 + c * 8 + (i & 1) * 4]);
                    mbar_wait(full0 + 8 * st, (t / kStages) & 1);
                    const uint32_t a = ring0 + st * kTileB + lane_off;
                    uint4 v[6];
#pragma unroll
                    for (int i = 0; i < 3; i++) { v[i] = lds128(a + i * 128); v[3 + i] = lds128(a + 4 * kRowB + i * 128); }
                    const float s0 = dot8(q[0], q[1], v[0]) + dot8(q[2], q[3], v[1]) + dot8(q[4], q[5], v[2]);
                    const float s1 = dot8(q[0], q[1], v[3]) + dot8(q[2], q[3], v[4]) + dot8(q[4], q[5], v[5]);
                    __syncwarp();
                    if (lane == 0) mbar_arrive(empty0 + 8 * st);
                    float mine = (c & 4) ? s1 : s0;
                    const float other = (c & 4) ? s0 : s1;
                    mine += __shfl_xor_sync(0xffffffffu, other, 4);
                    mine += __shfl_xor_sync(0xffffffffu, mine, 2);
                    mine += __shfl_xor_sync(0xffffffffu, mine, 1);
                    if ((c & 3) == 0) sm.sc[j][warp * 8 + c + g] = bfr(bfr(mine) * scale);
                }
            }
            bar_sync(kBarCons, 256);
            {
                float4 sv = *reinterpret_cast<const float4*>(&sm.sc[0][tid * 4]);
                float m = fmaxf(fmaxf(sv.x, sv.y), fmaxf(sv.z, sv.w));
#pragma unroll
                for (int o = 8; o > 0; o >>= 1) m = fmaxf(m, __shfl_xor_sync(0xffffffffu, m, o));
                sv.x = __expf(sv.x - m); sv.y = __expf(sv.y - m); sv.z = __expf(sv.z - m); sv.w = __expf(sv.w - m);
                *reinterpret_cast<uint2*>(&sm.rowc[tid * 4]) = make_uint2(pack_bf16(sv.x, sv.y), pack_bf16(sv.z, sv.w));
                float l = (sv.x + sv.y) + (sv.z + sv.w);
#pragma unroll
                for (int o = 8; o > 0; o >>= 1) l += __shfl_xor_sync(0xffffffffu, l, o);
                if ((lane & 15) == 0) { sm.stat[(tid >> 4) * 2] = m; sm.stat[(tid >> 4) * 2 + 1] = l; }
            }
        }

        if (warp < 5) {
            const uint32_t* cw = reinterpret_cast<const uint32_t*>(sm.coef);
            int tqp = tq;
            asm volatile("" : "+r"(tqp));
            const bool q0 = tqp == 0, q1 = tqp == 1;
            float4* slot = acc_slot(p.g, (((cta & 1) * 5 + warp) * 8 + mg) * 3 + tq);
            __nv_bfloat16* o = p.out + ((cta & 1) * 5 + warp) * 64 + tq * 24 + mg;
            float d[4][4];
            uint32_t off[4], w0[8][4], w1[8][4];
            float f0, f1, f2;
#pragma unroll
            for (int i = 0; i < 4; i++) off[i] = lk * 128 + ((((2 * i + ((lane >> 3) & 1)) ^ lk) & 7) << 4);
            {
                const uint32_t b0 = cw[48 + tq], b1 = cw[52 + tq], b2 = cw[56 + tq], b3 = cw[60 + tq];
                const float gb = sm.gate[1];
                const uint32_t a = ring0 + (kTD % kStages) * kTileB + warp * kFC * 128;
                mbar_wait(full0 + 8 * (kTD % kStages), (kTD / kStages) & 1);
#pragma unroll
                for (int i = 0; i < 4; i++) {
                    ldsm4t(w0[i], a + off[i]);
                    ldsm4t(w0[4 + i], a + off[i] + (lane < 16 ? 16 : 8) * 128);
                }
#pragma unroll
                for (int i = 0; i < 4; i++) {
                    d[i][0] = d[i][1] = d[i][2] = d[i][3] = 0.f;
                    mma16816(d[i], w0[i], b0, b1);
                    mma16816(d[i], w0[4 + i], b2, b3);
                }
                f0 = gb * fsel(q0, d[0][0], fsel(q1, d[1][2], d[3][0]));
                f1 = gb * fsel(q0, d[0][2], fsel(q1, d[2][0], d[3][2]));
                f2 = gb * fsel(q0, d[1][0], d[2][2]);
            }
#pragma unroll
            for (int i = 0; i < 4; i++) off[i] += ring0 + warp * 32 * 128;
            asm volatile("" : "+r"(off[0]), "+r"(off[1]), "+r"(off[2]), "+r"(off[3]));
            mbar_wait(full0 + 8 * (kTO % kStages), (kTO / kStages) & 1);
#pragma unroll
            for (int i = 0; i < 8; i++) ldsm4t(w0[i], off[i & 3] + (kTO % kStages) * kTileB + (i >> 2) * 2048);
            uint32_t b[12];
            float ga = sm.gate[0];
#pragma unroll
            for (int i = 0; i < 4; i++) d[i][0] = d[i][1] = d[i][2] = d[i][3] = 0.f;
            const bool early = __all_sync(0xffffffffu, mbar_test(s2u(&sm.coef_ready), 0));
            if (early) {
#pragma unroll
                for (int j = 0; j < 12; j++) b[j] = cw[j * 4 + tq];
#pragma unroll
                for (int i = 0; i < 8; i++) mma16816(d[i & 3], w0[i], b[(i >> 2) * 2], b[(i >> 2) * 2 + 1]);
            }
            asm volatile("" : "+l"(slot), "+l"(o), "+f"(ga), "+f"(f0), "+f"(f1), "+f"(f2));
            mbar_wait(full0 + 8 * ((kTO + 1) % kStages), ((kTO + 1) / kStages) & 1);
#pragma unroll
            for (int i = 0; i < 8; i++) ldsm4t(w1[i], off[i & 3] + ((kTO + 1) % kStages) * kTileB + (i >> 2) * 2048);
            if (!early) {
                mbar_wait(s2u(&sm.coef_ready), 0);
#pragma unroll
                for (int j = 0; j < 12; j++) b[j] = cw[j * 4 + tq];
#pragma unroll
                for (int i = 0; i < 8; i++) mma16816(d[i & 3], w0[i], b[(i >> 2) * 2], b[(i >> 2) * 2 + 1]);
            }
#pragma unroll
            for (int i = 0; i < 8; i++) mma16816(d[i & 3], w1[i], b[4 + (i >> 2) * 2], b[5 + (i >> 2) * 2]);
            mbar_wait(full0 + 8 * ((kTO + 2) % kStages), ((kTO + 2) / kStages) & 1);
#pragma unroll
            for (int i = 0; i < 8; i++) ldsm4t(w0[i], off[i & 3] + ((kTO + 2) % kStages) * kTileB + (i >> 2) * 2048);
#pragma unroll
            for (int i = 0; i < 8; i++) mma16816(d[i & 3], w0[i], b[8 + (i >> 2) * 2], b[9 + (i >> 2) * 2]);
            const float v0 = fmaf(ga, fsel(q0, d[0][0], fsel(q1, d[1][2], d[3][0])), f0);
            const float v1 = fmaf(ga, fsel(q0, d[0][2], fsel(q1, d[2][0], d[3][2])), f1);
            const float v2 = fmaf(ga, fsel(q0, d[1][0], d[2][2]), f2);
            if (tqp < 3) {
                const float4 old = atom_add4(slot, v0, v1, v2, 1.0f);
                if (old.w == (float)(kCTAs / 2 - 1)) {
                    st_bf16(o, old.x + v0);
                    st_bf16(o + 8, old.y + v1);
                    if (tqp < 2) st_bf16(o + 16, old.z + v2);
                }
            }
        }
        if (warp < 6) return;
    }

    {
        const int tt = warp == kCW + 1 ? 64 + lane : tid - 192;
        const int half = (cta >> 1) & 1;
        bar_sync(kBarTeam, 96);
        mbar_wait(s2u(&sm.go[1]), 0);
        if (hl >= kGH - kLate) {
            if (tt < kOC / 2) {
                float4* slot = acc_slot(p.g, kSlots + ((cta >> 6) * kLate + hl - (kGH - kLate)) * kOSlots + half * (kOC / 2) + tt);
                float4 r;
                unsigned n = 0;
                do { r = atom_add4(slot, 0.f, 0.f, 0.f, 0.f); if (++n > kSpinLimit) __trap(); } while (r.w != (float)kGrp);
                const int d = (tt >> 4) * 32 + (tt & 1) * 16 + ((tt >> 1) & 7);
                sm.coef[d] = __float2bfloat16_rn(r.x);
                sm.coef[d + 8] = __float2bfloat16_rn(r.y);
            }
        } else {
            const int c = tt % 24, sg = tt / 24;
            const unsigned* const ps[1] = {&p.g->omail[hl][cta0 + sg][half * kOC + c * 4]};
            Chunk r[16];
            mail_gather<16>(ps, 4 * kDh, tag, r);
            float4 acc = make_float4(0.f, 0.f, 0.f, 0.f);
#pragma unroll
            for (int k = 0; k < 16; k++) {
                const float w = sm.wgt[sg + 4 * k];
                acc.x = fmaf(w, r[k].v(0), acc.x); acc.y = fmaf(w, r[k].v(1), acc.y);
                acc.z = fmaf(w, r[k].v(2), acc.z); acc.w = fmaf(w, r[k].v(3), acc.w);
            }
            *reinterpret_cast<float4*>(&sm.part[sg][c * 4]) = acc;
            bar_sync(kBarTeam, 96);
            if (tt < kOC / 2) {
                const float2 a = *reinterpret_cast<const float2*>(&sm.part[0][tt * 2]), b = *reinterpret_cast<const float2*>(&sm.part[1][tt * 2]);
                const float2 e = *reinterpret_cast<const float2*>(&sm.part[2][tt * 2]), f = *reinterpret_cast<const float2*>(&sm.part[3][tt * 2]);
                reinterpret_cast<uint32_t*>(sm.coef)[tt] = pack_bf16((a.x + b.x) + (e.x + f.x), (a.y + b.y) + (e.y + f.y));
            }
        }
        __syncwarp();
        if (tt < 64 && lane == 0) mbar_arrive(s2u(&sm.coef_ready));
    }
}

__device__ float g_fb[2 * kH * kDh + kF];
__device__ __forceinline__ float ldbf(const void* p, size_t i) { return __bfloat162float(reinterpret_cast<const __nv_bfloat16*>(p)[i]); }
__global__ void fb_proj(const void* x, const void* wq, const void* wg, const void* wu) {
    const int n = blockIdx.x * blockDim.x + threadIdx.x;
    if (n < kH * kDh) {
        float a = 0.f;
        for (int k = 0; k < kD; k++) a = fmaf(ldbf(x, k), ldbf(wq, (size_t)k * kH * kDh + n), a);
        g_fb[n] = bfr(a);
    } else if (n < kH * kDh + kF) {
        const int f = n - kH * kDh;
        float a = 0.f, b = 0.f;
        for (int k = 0; k < kD; k++) { a = fmaf(ldbf(x, k), ldbf(wg, (size_t)k * kF + f), a); b = fmaf(ldbf(x, k), ldbf(wu, (size_t)k * kF + f), b); }
        a = bfr(a);
        g_fb[2 * kH * kDh + f] = bfr((a > 0.f ? a : a * 0.f) * bfr(b));
    }
}
__global__ void fb_attn(const void* kc, const void* vc) {
    __shared__ float sc[kW], red[kDh];
    const int h = blockIdx.x, t = threadIdx.x;
    const size_t base = ((size_t)h * kSk + kSk - kW) * kDh;
    float m = -INFINITY, l = 0.f, o = 0.f;
    for (int k = t; k < kW; k += kDh) {
        float a = 0.f;
        for (int d = 0; d < kDh; d++) a = fmaf(g_fb[h * kDh + d], ldbf(kc, base + (size_t)k * kDh + d), a);
        sc[k] = bfr(bfr(a) * 0.07216878364870322f);
        m = fmaxf(m, sc[k]);
    }
    red[t] = m;
    __syncthreads();
    for (int i = 0; i < kDh; i++) m = fmaxf(m, red[i]);
    for (int k = 0; k < kW; k++) {
        const float e = __expf(sc[k] - m);
        l += e;
        o = fmaf(e, ldbf(vc, base + (size_t)k * kDh + t), o);
    }
    g_fb[kH * kDh + h * kDh + t] = bfr(o / l);
}
__global__ void fb_out(const void* x, const void* gw, const void* wo, const void* wd, __nv_bfloat16* out) {
    const int n = blockIdx.x * blockDim.x + threadIdx.x;
    float z = 0.f, a = 0.f, b = 0.f;
    for (int k = 0; k < kD; k++) z += bfr(ldbf(x, k) * ldbf(gw, k));
    const float g = bfr(1.0f / (1.0f + __expf(-bfr(z))));
    for (int k = 0; k < kH * kDh; k++) a = fmaf(g_fb[kH * kDh + k], ldbf(wo, (size_t)k * kD + n), a);
    for (int k = 0; k < kF; k++) b = fmaf(g_fb[2 * kH * kDh + k], ldbf(wd, (size_t)k * kD + n), b);
    out[n] = __float2bfloat16_rn(g * a + bfr(1.0f - g) * b);
}

typedef CUresult (*EncodeFn)(CUtensorMap*, CUtensorMapDataType, cuuint32_t, void*, const cuuint64_t*, const cuuint64_t*,
                             const cuuint32_t*, const cuuint32_t*, CUtensorMapInterleave, CUtensorMapSwizzle,
                             CUtensorMapL2promotion, CUtensorMapFloatOOBfill);

void make_map(EncodeFn fn, CUtensorMap* m, void* base, int rows, int cols, int box_rows) {
    const cuuint64_t dims[3] = {64, (cuuint64_t)(cols / 64), (cuuint64_t)rows};
    const cuuint64_t strides[2] = {128, (cuuint64_t)cols * 2};
    const cuuint32_t box[3] = {64, 3, (cuuint32_t)box_rows};
    const cuuint32_t estr[3] = {1, 1, 1};
    fn(m, CU_TENSOR_MAP_DATA_TYPE_BFLOAT16, 3, base, dims, strides, box, estr, CU_TENSOR_MAP_INTERLEAVE_NONE,
       CU_TENSOR_MAP_SWIZZLE_128B, CU_TENSOR_MAP_L2_PROMOTION_NONE, CU_TENSOR_MAP_FLOAT_OOB_FILL_NONE);
}
void make_map_out(EncodeFn fn, CUtensorMap* m, void* base, int rows, int box_rows) {
    const cuuint64_t dims[3] = {64, (cuuint64_t)rows, (cuuint64_t)(kD / 64)};
    const cuuint64_t strides[2] = {(cuuint64_t)kOutRowB, 128};
    const cuuint32_t box[3] = {64, (cuuint32_t)box_rows, 5};
    const cuuint32_t estr[3] = {1, 1, 1};
    fn(m, CU_TENSOR_MAP_DATA_TYPE_BFLOAT16, 3, base, dims, strides, box, estr, CU_TENSOR_MAP_INTERLEAVE_NONE,
       CU_TENSOR_MAP_SWIZZLE_128B, CU_TENSOR_MAP_L2_PROMOTION_NONE, CU_TENSOR_MAP_FLOAT_OOB_FILL_NONE);
}

}

extern "C" void kernel_launch(void* const* d_in, const int* in_sizes, int n_in, void* d_out, int out_size) {
    (void)in_sizes; (void)n_in; (void)out_size;
    static EncodeFn encode = nullptr;
    static void* scratch = nullptr;
    static int resident = -1;
    if (resident < 0) {
        cudaGetSymbolAddress(&scratch, g_scratch);
        void* fn = nullptr;
        cudaDriverEntryPointQueryResult qr;
        cudaGetDriverEntryPoint("cuTensorMapEncodeTiled", &fn, cudaEnableDefault, &qr);
        encode = (EncodeFn)fn;
        cudaFuncSetAttribute(fused_decode_kernel, cudaFuncAttributeMaxDynamicSharedMemorySize, (int)sizeof(Smem));
        int dev = 0, sms = 0, per_sm = 0;
        cudaGetDevice(&dev);
        cudaDeviceGetAttribute(&sms, cudaDevAttrMultiProcessorCount, dev);
        cudaOccupancyMaxActiveBlocksPerMultiprocessor(&per_sm, fused_decode_kernel, kThreads, sizeof(Smem));
        resident = sms * per_sm;
    }
    if (resident < kCTAs || !encode) {
        fb_proj<<<(kH * kDh + kF) / 128, 128, 0, cudaStreamPerThread>>>(d_in[0], d_in[3], d_in[6], d_in[7]);
        fb_attn<<<kH, kDh, 0, cudaStreamPerThread>>>(d_in[1], d_in[2]);
        fb_out<<<kD / 32, 32, 0, cudaStreamPerThread>>>(d_in[0], d_in[9], d_in[4], d_in[8], (__nv_bfloat16*)d_out);
        return;
    }
    Params p;
    p.x = (const __nv_bfloat16*)d_in[0];
    p.k = (const unsigned char*)d_in[1];
    p.gate_w = (const __nv_bfloat16*)d_in[9];
    p.out = (__nv_bfloat16*)d_out;
    p.g = (Scratch*)scratch;
    make_map(encode, &p.tq, d_in[3], kD, kH * kDh, 32);
    make_map(encode, &p.tg, d_in[6], kD, kF, 16);
    make_map(encode, &p.tu, d_in[7], kD, kF, 16);
    make_map(encode, &p.tv, d_in[2], kH * kSk, kDh, kTileKeys);
    make_map_out(encode, &p.td, d_in[8], kF, kFC);
    make_map_out(encode, &p.to, d_in[4], kH * kDh, 32);
    fused_decode_kernel<<<kCTAs, kThreads, sizeof(Smem), cudaStreamPerThread>>>((const unsigned char*)d_in[3], p);
}
```

```cpp
#include <cuda_runtime.h>
#include <cuda_bf16.h>
#include <cuda.h>
#include <math.h>
#include <stdint.h>

namespace {

constexpr int kD = 640;
constexpr int kH = 32;
constexpr int kDh = 192;
constexpr int kSk = 32768;
constexpr int kW = 4096;
constexpr int kF = 1536;
constexpr int kCTAs = 128;
constexpr int kGrp = 64;
constexpr int kGH = kH * kGrp / kCTAs;
constexpr int kCW = 8;
constexpr int kThreads = kCW * 32 + 64;
constexpr int kTileKeys = kW / kGrp;
constexpr int kRowB = kDh * 2;
constexpr int kTileB = kTileKeys * kRowB;
constexpr int kStages = 8;
constexpr int kOutRowB = kD * 2;
constexpr int kFC = 2 * kF / kCTAs;
constexpr int kOC = 2 * kH * kDh / kCTAs;
constexpr int kXR = kD / 4;
constexpr int kFR = kD / 8;
constexpr int kTQ = 0;
constexpr int kTK = 3;
constexpr int kTF = kTK + kGH;
constexpr int kTV = kTF + 2;
constexpr int kTD = kTV + kGH;
constexpr int kTO = kTD + 1;
constexpr int kNumTiles = kTO + 3;
constexpr int kSlots = 240;
constexpr int kLate = 4;
constexpr int kOSlots = kDh / 2;
constexpr int kAccSlots = kSlots + 2 * kLate * kOSlots;
constexpr unsigned kSpinLimit = 1u << 24;
static_assert(kTD - kLate + kStages > kNumTiles - 1, "the producer must be able to finish before the late V tiles are consumed");

constexpr uint32_t kWindow = 71000;
constexpr int kBalStart = 8;
constexpr int kLead0 = 16, kLead1 = 72, kLead2 = 128;
constexpr int kMile = 576, kMileLate = 384;
constexpr unsigned kMileQ = 400;

constexpr int kCbQ = kGH * kTileKeys, kCbF = kCbQ + kXR, kCbLen = kCbF + kFR;

struct Smem {
    alignas(1024) unsigned char ring[kStages][kTileB];
    alignas(16) float q[kGH][kDh];
    alignas(16) float sc[kGH][kTileKeys];
    alignas(16) __nv_bfloat16 rowc[kCbLen];
    alignas(16) __nv_bfloat16 coef[128];
    alignas(16) float part[4][kOC];
    float wgt[kGrp];
    float lscale[kLate];
    float stat[2 * kGH];
    float gate[2];
    unsigned tag;
    alignas(8) unsigned long long full[kStages];
    alignas(8) unsigned long long empty[kStages];
    alignas(8) unsigned long long coef_ready;
    alignas(8) unsigned long long go[2];
};

struct Scratch {
    alignas(256) unsigned epoch;
    alignas(256) unsigned accflag;
    alignas(256) unsigned prog;
    alignas(256) float4 acc[kAccSlots * 4];
    alignas(256) unsigned stat[kCTAs][2 * kGH];
    alignas(256) unsigned qmail[kCTAs][kDh];
    alignas(256) unsigned fmail[kCTAs][kDh];
    alignas(256) unsigned omail[kGH - kLate][kCTAs][kDh];
};
__device__ Scratch g_scratch;

__device__ __forceinline__ uint32_t s2u(const void* p) { return (uint32_t)__cvta_generic_to_shared(p); }

__device__ __forceinline__ void mbar_init(uint32_t bar, uint32_t cnt) {
    asm volatile("mbarrier.init.shared::cta.b64 [%0], %1;" ::"r"(bar), "r"(cnt) : "memory");
}
__device__ __forceinline__ void mbar_expect_tx(uint32_t bar, uint32_t bytes) {
    asm volatile("mbarrier.arrive.expect_tx.shared::cta.b64 _, [%0], %1;" ::"r"(bar), "r"(bytes) : "memory");
}
__device__ __forceinline__ void mbar_arrive(uint32_t bar, uint32_t cnt = 1) {
    asm volatile("mbarrier.arrive.shared::cta.b64 _, [%0], %1;" ::"r"(bar), "r"(cnt) : "memory");
}
__device__ __forceinline__ void mbar_wait(uint32_t bar, uint32_t parity) {
    asm volatile("{\n.reg .pred p;\n.reg .u32 n;\nmov.u32 n, 0;\n"
                 "WL:\nmbarrier.try_wait.parity.shared::cta.b64 p, [%0], %1;\n@p bra WD;\n"
                 "add.u32 n, n, 1;\nsetp.lt.u32 p, n, %2;\n@p bra WL;\ntrap;\nWD:\n}"
                 ::"r"(bar), "r"(parity), "n"(kSpinLimit) : "memory");
}
__device__ __forceinline__ bool mbar_test(uint32_t bar, uint32_t parity) {
    uint32_t ok;
    asm volatile("{\n.reg .pred p;\nmbarrier.test_wait.parity.shared::cta.b64 p, [%1], %2;\nselp.u32 %0, 1, 0, p;\n}"
                 : "=r"(ok) : "r"(bar), "r"(parity) : "memory");
    return ok != 0;
}
__device__ __forceinline__ void bulk_g2s(uint32_t dst, const void* src, uint32_t bytes, uint32_t bar, uint64_t pol) {
    asm volatile("cp.async.bulk.shared::cluster.global.mbarrier::complete_tx::bytes.L2::cache_hint [%0], [%1], %2, [%3], %4;"
                 ::"r"(dst), "l"(src), "r"(bytes), "r"(bar), "l"(pol) : "memory");
}
__device__ __forceinline__ void tma_3d(uint32_t dst, const CUtensorMap* map, int c1, int c2, uint32_t bar, uint64_t pol) {
    asm volatile("cp.async.bulk.tensor.3d.shared::cluster.global.mbarrier::complete_tx::bytes.L2::cache_hint [%0], [%1, {%4, %3, %6}], [%2], %5;"
                 ::"r"(dst), "l"(map), "r"(bar), "r"(c1), "r"(0), "l"(pol), "r"(c2) : "memory");
}
__device__ __forceinline__ void ldsm4t(uint32_t (&r)[4], uint32_t a) {
    asm volatile("ldmatrix.sync.aligned.m8n8.x4.trans.shared.b16 {%0,%1,%2,%3}, [%4];"
                 : "=r"(r[0]), "=r"(r[1]), "=r"(r[2]), "=r"(r[3]) : "r"(a));
}
__device__ __forceinline__ void mma16816(float (&d)[4], const uint32_t (&a)[4], uint32_t b0, uint32_t b1) {
    asm volatile("mma.sync.aligned.m16n8k16.row.col.f32.bf16.bf16.f32 {%0,%1,%2,%3}, {%4,%5,%6,%7}, {%8,%9}, {%0,%1,%2,%3};"
                 : "+f"(d[0]), "+f"(d[1]), "+f"(d[2]), "+f"(d[3]) : "r"(a[0]), "r"(a[1]), "r"(a[2]), "r"(a[3]), "r"(b0), "r"(b1));
}
__device__ __forceinline__ uint4 ldg128(const void* p) {
    uint4 v;
    asm volatile("ld.global.nc.v4.u32 {%0,%1,%2,%3}, [%4];" : "=r"(v.x), "=r"(v.y), "=r"(v.z), "=r"(v.w) : "l"(p));
    return v;
}
__device__ __forceinline__ uint4 lds128(uint32_t a) {
    uint4 v;
    asm volatile("ld.shared.v4.u32 {%0,%1,%2,%3}, [%4];" : "=r"(v.x), "=r"(v.y), "=r"(v.z), "=r"(v.w) : "r"(a));
    return v;
}

__device__ __forceinline__ void word_st(unsigned* p, float v, unsigned tag) {
    asm volatile("st.relaxed.gpu.global.u32 [%0], %1;" ::"l"(p), "r"((__float_as_uint(v) & ~3u) | tag) : "memory");
}
__device__ __forceinline__ float word_val(unsigned w) { return __uint_as_float(w & ~3u); }
struct Chunk {
    unsigned w[4];
    __device__ __forceinline__ float v(int i) const { return word_val(w[i]); }
};
__device__ __forceinline__ unsigned mail_poll(const unsigned* p) {
    unsigned r;
    asm volatile("atom.relaxed.gpu.global.or.b32 %0, [%1], 0;" : "=r"(r) : "l"(p) : "memory");
    return r;
}
template <int N, int NP = N>
__device__ __forceinline__ void mail_gather(const unsigned* const (&p)[N / NP], int stride, unsigned tag, Chunk (&r)[N]) {
#pragma unroll
    for (int i = 0; i < N; i++) {
        asm volatile("ld.relaxed.gpu.global.v4.u32 {%0,%1,%2,%3}, [%4];"
                     : "=r"(r[i].w[0]), "=r"(r[i].w[1]), "=r"(r[i].w[2]), "=r"(r[i].w[3])
                     : "l"(p[i / NP] + (i % NP) * stride) : "memory");
    }
    unsigned n = 0;
#pragma unroll 1
    while (true) {
        unsigned bad = 0;
#pragma unroll
        for (int i = 0; i < N; i++)
            bad |= (((r[i].w[0] ^ tag) | (r[i].w[1] ^ tag) | (r[i].w[2] ^ tag) | (r[i].w[3] ^ tag)) & 3u) ? 1u << i : 0u;
        bad = __reduce_or_sync(0xffffffffu, bad);
        if (bad == 0) break;
        __nanosleep(200);
#pragma unroll
        for (int i = 0; i < N; i++) {
            if (bad >> i & 1) {
#pragma unroll
                for (int e = 0; e < 4; e++) r[i].w[e] = mail_poll(p[i / NP] + (i % NP) * stride + e);
            }
        }
        if (++n > kSpinLimit) __trap();
    }
}
__device__ __forceinline__ void word_wait(const unsigned* p, unsigned tag) {
    unsigned n = 0;
    while ((mail_poll(p) ^ tag) & 3u) { __nanosleep(100); if (++n > kSpinLimit) __trap(); }
}

__device__ __forceinline__ float4 atom_add4(float4* p, float a, float b, float c, float d) {
    float4 r;
    asm volatile("atom.relaxed.gpu.global.add.v4.f32 {%0,%1,%2,%3}, [%4], {%5,%6,%7,%8};"
                 : "=f"(r.x), "=f"(r.y), "=f"(r.z), "=f"(r.w) : "l"(p), "f"(a), "f"(b), "f"(c), "f"(d) : "memory");
    return r;
}
__device__ __forceinline__ float4* acc_slot(Scratch* g, int i) { return &g->acc[(i >> 2) * 16 + (i & 3)]; }

enum { kBarCons = 1, kBarStart = 2, kBarStats = 3, kBarScalars = 4, kBarTeam = 5, kBarInit = 6 };
__device__ __forceinline__ void bar_sync(int id, int n) { asm volatile("barrier.sync %0, %1;" ::"r"(id), "r"(n) : "memory"); }
__device__ __forceinline__ void bar_arrive(int id, int n) { asm volatile("barrier.arrive %0, %1;" ::"r"(id), "r"(n) : "memory"); }

__device__ __forceinline__ void st_bf16(__nv_bfloat16* p, float v) {
    asm volatile("st.global.u16 [%0], %1;" ::"l"(p), "h"(__bfloat16_as_ushort(__float2bfloat16_rn(v))) : "memory");
}
__device__ __forceinline__ float fsel(bool c, float a, float b) {
    float r;
    asm("{\n.reg .pred p;\nsetp.ne.u32 p, %3, 0;\nselp.f32 %0, %1, %2, p;\n}" : "=f"(r) : "f"(a), "f"(b), "r"((unsigned)c));
    return r;
}
__device__ __forceinline__ float bf_lo(uint32_t w) { return __uint_as_float(w << 16); }
__device__ __forceinline__ float bf_hi(uint32_t w) { return __uint_as_float(w & 0xffff0000u); }
__device__ __forceinline__ float bfr(float v) { return __bfloat162float(__float2bfloat16_rn(v)); }
__device__ __forceinline__ uint32_t pack_bf16(float lo, float hi) {
    const __nv_bfloat162 v = __floats2bfloat162_rn(lo, hi);
    return *reinterpret_cast<const uint32_t*>(&v);
}
__device__ __forceinline__ float dot8(const float4& qa, const float4& qb, const uint4& v) {
    float a = qa.x * bf_lo(v.x), b = qa.y * bf_hi(v.x);
    a = fmaf(qa.z, bf_lo(v.y), a); b = fmaf(qa.w, bf_hi(v.y), b);
    a = fmaf(qb.x, bf_lo(v.z), a); b = fmaf(qb.y, bf_hi(v.z), b);
    a = fmaf(qb.z, bf_lo(v.w), a); b = fmaf(qb.w, bf_hi(v.w), b);
    return a + b;
}
__device__ __forceinline__ bool elect_one() {
    uint32_t ok;
    asm volatile("{\n.reg .pred p;\nelect.sync _|p, 0xffffffff;\nselp.u32 %0, 1, 0, p;\n}" : "=r"(ok));
    return ok != 0;
}

__host__ __device__ constexpr uint32_t tile_bytes(int t) {
    return (t == kTQ + 2 || t == kTF + 1) ? 32 * kRowB
         : t == kTF ? 48 * kRowB
         : t == kTD ? kFC * kOutRowB / 2
         : t >= kTO ? 32 * kOutRowB / 2 : kTileB;
}
constexpr uint64_t pack_back(int first) {
    uint64_t r = 0;
    for (int t = first; t < first + 21 && t < kNumTiles; t++) {
        uint32_t sum = 0;
        int j = t;
        for (; j >= 0; j--) { sum += tile_bytes(j); if (sum > kWindow) break; }
        r |= (uint64_t)(t - j > 5 ? 5 : t - j) << (3 * (t - first));
    }
    return r;
}
constexpr uint64_t kBackA = pack_back(0), kBackB = pack_back(21);
__device__ __forceinline__ int look_back(int t) {
    return (int)(((t < 21 ? kBackA : kBackB) >> (3 * (t < 21 ? t : t - 21))) & 7);
}

struct Params {
    const __nv_bfloat16* x;
    const unsigned char* k;
    const __nv_bfloat16* gate_w;
    __nv_bfloat16* out;
    Scratch* g;
    CUtensorMap tq;
    CUtensorMap tg;
    CUtensorMap tu;
    CUtensorMap tv;
    CUtensorMap td;
    CUtensorMap to;
};

__global__ void __launch_bounds__(kThreads, 1)
fused_decode_kernel(const unsigned char* __restrict__ wq, const __grid_constant__ Params p) {
    if (threadIdx.x == 0)
        asm volatile("cp.async.bulk.prefetch.L2.global [%0], %1;"
                     ::"l"(wq + (size_t)((blockIdx.x >> 5) * kXR + (blockIdx.x & 31)) * (kH * kRowB)), "n"(kH * kRowB) : "memory");
    extern __shared__ __align__(1024) unsigned char smem_raw[];
    Smem& sm = *reinterpret_cast<Smem*>(smem_raw);
    const int tid = threadIdx.x;
    const int lane = tid & 31;
    const int warp = tid >> 5;
    const int cta = blockIdx.x;
    const int cta0 = cta & ~(kGrp - 1);
    const int hl = (cta >> 2) & (kGH - 1);
    const uint32_t ring0 = s2u(&sm.ring[0][0]);
    const uint32_t full0 = s2u(&sm.full[0]);
    const uint32_t empty0 = s2u(&sm.empty[0]);

    uint64_t pol;
    asm volatile("createpolicy.fractional.L2::evict_first.b64 %0, 1.0;" : "=l"(pol));
    if (warp == kCW && elect_one()) {
#pragma unroll
        for (int i = 0; i < kTK; i++) mbar_init(full0 + 8 * i, 1);
        asm volatile("fence.mbarrier_init.release.cluster;" ::: "memory");
#pragma unroll
        for (int i = 0; i < kTK; i++) {
            const int row = (cta & 3) * kXR + i * 64;
            mbar_expect_tx(full0 + 8 * i, tile_bytes(i));
            tma_3d(ring0 + i * kTileB, &p.tq, (cta >> 2) * 3, row, full0 + 8 * i, pol);
            if (i < 2) tma_3d(ring0 + i * kTileB + 32 * kRowB, &p.tq, (cta >> 2) * 3, row + 32, full0 + 8 * i, pol);
        }
    }
    __syncwarp();

    if (warp == kCW) {
        const bool leader = elect_one();
        bar_sync(kBarInit, 64);
        bar_arrive(kBarStart, kThreads);
        const int key0 = (cta >> 6) * kGH * kSk + (kSk - kW) + (cta & (kGrp - 1)) * kTileKeys;
        const unsigned char* src = p.k + (size_t)key0 * kRowB;
        constexpr unsigned kProgMax = (kNumTiles - kTK) * kCTAs - 1;
        unsigned prog = 0;
        constexpr int kNever = 1 << 30;
        int mile0 = (kTV - 1 - kTK) * kCTAs + kMile, mile1 = (kTV + hl - kTK) * kCTAs + (hl < kGH - kLate ? kMile : kMileLate);
#pragma unroll 1
        for (int t = kTK; t < kNumTiles; t++) {
            const uint32_t st = t % kStages;
            const uint32_t dst = ring0 + st * kTileB, bar = full0 + 8 * st;
            if (t >= kStages) mbar_wait(empty0 + 8 * st, ((t / kStages) - 1) & 1);
            if (leader) mbar_expect_tx(bar, tile_bytes(t));
            int need = t - look_back(t);
            if (t >= kBalStart) {
                const int gp = (int)__shfl_sync(0xffffffffu, prog, 0);
                const int lead = (t - kTK) * kCTAs - gp;
                need += (lead > kLead2) - (lead <= kLead1) - (lead <= kLead0);
                const int seen = t == kNumTiles - 1 ? kNever - 1 : gp;
                if (seen >= mile0) { mile0 = kNever; if (leader) mbar_arrive(s2u(&sm.go[0])); }
                if (seen >= mile1) { mile1 = kNever; if (leader) mbar_arrive(s2u(&sm.go[1])); }
            }
            if (need >= 0) mbar_wait(full0 + 8 * (need % kStages), (need / kStages) & 1);
            if (leader) {
                if (t < kTF) {
                    bulk_g2s(dst, src, kTileB, bar, pol);
                } else if (t < kTV) {
                    const CUtensorMap* m = cta < 64 ? &p.tg : &p.tu;
                    const int row = (cta & 7) * kFR + (t - kTF) * 48, blk = ((cta >> 3) & 7) * 3;
                    tma_3d(dst, m, blk, row, bar, pol);
                    tma_3d(dst + 16 * kRowB, m, blk, row + 16, bar, pol);
                    if (t == kTF) tma_3d(dst + 32 * kRowB, m, blk, row + 32, bar, pol);
                } else if (t < kTD) {
                    tma_3d(dst, &p.tv, 0, key0 + (t - kTV) * kSk, bar, pol);
                } else {
                    tma_3d(dst, t == kTD ? &p.td : &p.to, t == kTD ? (cta >> 1) * kFC : (cta >> 1) * kOC + (t - kTO) * 32,
                           (cta & 1) * 5, bar, pol);
                }
            }
            if (leader && t == 12) {
                asm volatile("prefetch.tensormap [%0];" ::"l"(cta < 64 ? &p.tg : &p.tu) : "memory");
                asm volatile("prefetch.tensormap [%0];" ::"l"(&p.tv) : "memory");
                asm volatile("prefetch.tensormap [%0];" ::"l"(&p.td) : "memory");
                asm volatile("prefetch.tensormap [%0];" ::"l"(&p.to) : "memory");
            }
            src += (size_t)kSk * kRowB;
            if (lane == 0) {
                if (t + 1 >= kBalStart)
                    asm volatile("atom.relaxed.gpu.global.inc.u32 %0, [%1], %2;" : "=r"(prog) : "l"(&p.g->prog), "n"(kProgMax) : "memory");
                else
                    asm volatile("red.relaxed.gpu.global.inc.u32 [%0], %1;" ::"l"(&p.g->prog), "n"(kProgMax) : "memory");
            }
        }
        if (lane == 0 && prog == kProgMax) p.g->epoch = sm.tag;
        return;
    }

    unsigned tag;
    if (warp == kCW + 1) {
        if (elect_one()) {
#pragma unroll
            for (int i = 0; i < kStages; i++) { if (i >= kTK) mbar_init(full0 + 8 * i, 1); mbar_init(empty0 + 8 * i, kCW); }
            mbar_init(s2u(&sm.coef_ready), 2);
            mbar_init(s2u(&sm.go[0]), 1);
            mbar_init(s2u(&sm.go[1]), 1);
            asm volatile("fence.mbarrier_init.release.cluster;" ::: "memory");
        }
        __syncwarp();
        bar_arrive(kBarInit, 64);
        unsigned e = 0;
        if (lane == 31) asm volatile("ld.relaxed.gpu.global.u32 %0, [%1];" : "=r"(e) : "l"(&p.g->epoch) : "memory");
        if (lane < 30) {
            const uint4 v = ldg128(p.x + (lane < 20 ? (cta & 3) * kXR + lane * 8 : (cta & 7) * kFR + (lane - 20) * 8));
            *reinterpret_cast<uint4*>(&sm.rowc[kCbQ + lane * 8]) = v;
        }
        tag = __shfl_sync(0xffffffffu, e, 31) % 3u + 1u;
        if (lane == 0) sm.tag = tag;
        bar_arrive(kBarStart, kThreads);
        __nanosleep(3000);
        if (cta == 0) {
            for (int i = lane; i < kAccSlots; i += 32) *acc_slot(p.g, i) = make_float4(0.f, 0.f, 0.f, 0.f);
            __threadfence();
            __syncwarp();
            if (lane == 0) { __threadfence(); word_st(&p.g->accflag, 0.f, tag); }
        }
        {
            float z = 0.f;
#pragma unroll 1
            for (int j = lane; j < kD / 8; j += 32) {
                const uint4 gx = ldg128(p.x + j * 8), gw = ldg128(p.gate_w + j * 8);
                z += bfr(bf_lo(gx.x) * bf_lo(gw.x)) + bfr(bf_hi(gx.x) * bf_hi(gw.x));
                z += bfr(bf_lo(gx.y) * bf_lo(gw.y)) + bfr(bf_hi(gx.y) * bf_hi(gw.y));
                z += bfr(bf_lo(gx.z) * bf_lo(gw.z)) + bfr(bf_hi(gx.z) * bf_hi(gw.z));
                z += bfr(bf_lo(gx.w) * bf_lo(gw.w)) + bfr(bf_hi(gx.w) * bf_hi(gw.w));
            }
#pragma unroll
            for (int o = 16; o > 0; o >>= 1) z += __shfl_xor_sync(0xffffffffu, z, o);
            const float gate = bfr(1.0f / (1.0f + __expf(-bfr(z))));
            if (lane == 0) { sm.gate[0] = gate; sm.gate[1] = bfr(1.0f - gate); }
            if (lane < 8) sm.coef[kOC + kFC + lane] = __float2bfloat16_rn(0.f);
        }
        __nanosleep(2000);
        if (lane == 0) {
            word_wait(&p.g->accflag, tag);
            __threadfence();
        }
        __syncwarp();
        bar_sync(kBarStats, 288);
        word_st(&p.g->stat[cta][lane], sm.stat[lane], tag);
        mbar_wait(s2u(&sm.go[0]), 0);
        {
            const int mtx = lane >> 4, rb = (lane >> 1) & 7, half = lane & 1;
            const unsigned* sa = p.g->stat[cta0 + lane];
            const unsigned* sb = p.g->stat[cta0 + 32 + lane];
            const unsigned* fm = &p.g->fmail[(mtx * 8 + (cta >> 4)) * 8 + rb][((cta >> 1) & 7) * kFC + half * 12];
            const unsigned* const ps[9] = {sa + (hl >> 1) * 4, sb + (hl >> 1) * 4, sa + 24, sb + 24, sa + 28, sb + 28, fm, fm + 4, fm + 8};
            Chunk r[9];
            mail_gather<9, 1>(ps, 0, tag, r);
#pragma unroll 1
            for (int i = -1; i < kLate; i++) {
                const int hd = i < 0 ? hl : kGH - kLate + i;
                const Chunk a = i < 0 ? r[0] : hd < 14 ? r[2] : r[4], b = i < 0 ? r[1] : hd < 14 ? r[3] : r[5];
                const float m0 = hd & 1 ? a.v(2) : a.v(0), l0 = hd & 1 ? a.v(3) : a.v(1);
                const float m1 = hd & 1 ? b.v(2) : b.v(0), l1 = hd & 1 ? b.v(3) : b.v(1);
                float M = fmaxf(m0, m1);
#pragma unroll
                for (int o = 16; o > 0; o >>= 1) M = fmaxf(M, __shfl_xor_sync(0xffffffffu, M, o));
                const float w0 = __expf(m0 - M), w1 = __expf(m1 - M);
                float L = w0 * l0 + w1 * l1;
#pragma unroll
                for (int o = 16; o > 0; o >>= 1) L += __shfl_xor_sync(0xffffffffu, L, o);
                if (i < 0) { sm.wgt[lane] = w0 / L; sm.wgt[lane + 32] = w1 / L; }
                else if (lane == (cta & 31)) sm.lscale[i] = ((cta & 32) ? w1 : w0) / L;
            }
#pragma unroll
            for (int j = 0; j < 12; j++) {
                float v = r[6 + (j >> 2)].v(j & 3);
                v += __shfl_xor_sync(0xffffffffu, v, 2);
                v += __shfl_xor_sync(0xffffffffu, v, 4);
                v += __shfl_xor_sync(0xffffffffu, v, 8);
                const float gt = bfr(v);
                const float up = __shfl_xor_sync(0xffffffffu, gt, 16);
                if (lane < 2) sm.coef[kOC + half * 12 + j] = __float2bfloat16_rn((gt > 0.f ? gt : gt * 0.f) * up);
            }
        }
        bar_arrive(kBarScalars, 224);
    } else {
        bar_sync(kBarStart, kThreads);
        tag = sm.tag;

        const int mg = lane >> 2, tq = lane & 3;
        const int lk = (lane & 7) + ((lane >> 4) << 3);
        uint32_t voff[2];
#pragma unroll
        for (int i = 0; i < 2; i++) {
            const int line = lk * 3 + (warp >> 1);
            voff[i] = line * 128 + (((((warp & 1) * 4 + 2 * i + ((lane >> 3) & 1)) ^ line) & 7) << 4);
        }
#pragma unroll 1
        for (int pass = 0; pass < 3; pass++) {
            if (warp < 6) {
                const int t0 = pass == 0 ? kTQ : (pass == 1 ? kTF : kTV);
                const int t1 = pass == 0 ? kTK : (pass == 1 ? kTV : kTD);
                const uint32_t* cf = reinterpret_cast<const uint32_t*>(&sm.rowc[pass == 0 ? kCbQ : (pass == 1 ? kCbF : 0)]) + tq;
                float d[4][4];
#pragma unroll
                for (int i = 0; i < 4; i++) d[i][0] = d[i][1] = d[i][2] = d[i][3] = 0.f;
#pragma unroll 1
                for (int t = t0; t < t1; t++) {
                    const uint32_t st = t % kStages;
                    const int nk = tile_bytes(t) / (16 * kRowB);
                    if (t == kTD - kLate) bar_sync(kBarScalars, 224);
                    uint32_t b[8];
#pragma unroll
                    for (int j = 0; j < 8; j++) b[j] = cf[j * 4];
                    cf += nk * 8;
                    const bool late = t >= kTD - kLate;
                    const float ls = sm.lscale[late ? t - (kTD - kLate) : 0];
                    void* dst = late ? (void*)acc_slot(p.g, kSlots + ((cta >> 6) * kLate + t - (kTD - kLate)) * kOSlots + warp * 16 + mg * 2 + (tq >> 1))
                                     : (void*)((t < kTK ? p.g->qmail[cta] : t < kTV ? p.g->fmail[cta] : p.g->omail[t - kTV][cta]) + warp * 32 + tq * 8 + mg);
                    mbar_wait(full0 + 8 * st, (t / kStages) & 1);
                    const uint32_t a = ring0 + st * kTileB;
                    uint32_t w[8][4];
#pragma unroll
                    for (int j = 0; j < 4; j++) ldsm4t(w[j], a + voff[j & 1] + (j >> 1) * (16 * kRowB));
                    if (nk > 2) {
                        ldsm4t(w[4], a + voff[0] + 2 * (16 * kRowB));
                        ldsm4t(w[5], a + voff[1] + 2 * (16 * kRowB));
                    }
                    if (nk > 3) {
                        ldsm4t(w[6], a + voff[0] + 3 * (16 * kRowB));
                        ldsm4t(w[7], a + voff[1] + 3 * (16 * kRowB));
                    }
#pragma unroll
                    for (int j = 0; j < 4; j++) mma16816(d[j], w[j], b[(j >> 1) * 2], b[(j >> 1) * 2 + 1]);
                    if (nk > 2) { mma16816(d[0], w[4], b[4], b[5]); mma16816(d[1], w[5], b[4], b[5]); }
                    if (nk > 3) { mma16816(d[2], w[6], b[6], b[7]); mma16816(d[3], w[7], b[6], b[7]); }
                    if (pass == 2 || t == t1 - 1) {
                        const float c0 = fsel(tq & 2, d[1][0] + d[3][0], d[0][0] + d[2][0]);
                        const float c8 = fsel(tq & 2, d[1][2] + d[3][2], d[0][2] + d[2][2]);
                        if (!late) word_st((unsigned*)dst, fsel(tq & 1, c8, c0), tag);
                        else if (!(tq & 1))
                            asm volatile("red.relaxed.gpu.global.add.v4.f32 [%0], {%1,%2,%3,%4};"
                                         ::"l"(dst), "f"(c0 * ls), "f"(c8 * ls), "f"(0.f), "f"(1.f) : "memory");
#pragma unroll
                        for (int i = 0; i < 4; i++) d[i][0] = d[i][1] = d[i][2] = d[i][3] = 0.f;
                    }
                    __syncwarp();
                    if (lane == 0) mbar_arrive(empty0 + 8 * st, warp < 2 ? 2 : 1);
                }
            }
            if (pass == 1) bar_sync(kBarStats, 288);
            if (pass != 0) continue;

            if (tid == kDh) {
                mbar_wait(full0 + 8 * kTK, 0);
                for (int n = 0; n < 64 && mail_poll(&p.g->prog) < kMileQ; n++) __nanosleep(150);
            }
            bar_sync(kBarCons, 256);
            {
                Chunk r[12];
                const unsigned* ps_[3];
#pragma unroll
                for (int k = 0; k < 3; k++) {
                    const int id = tid + 256 * k, j = id / 48;
                    ps_[k] = &p.g->qmail[cta0 + j * 4][(id - j * 48) * 4];
                }
                const unsigned* const ps[3] = {ps_[0], ps_[1], ps_[2]};
                mail_gather<12, 4>(ps, kDh, tag, r);
#pragma unroll
                for (int k = 0; k < 3; k++) {
                    float v[4];
#pragma unroll
                    for (int e = 0; e < 4; e++) v[e] = bfr((r[k * 4].v(e) + r[k * 4 + 1].v(e)) + (r[k * 4 + 2].v(e) + r[k * 4 + 3].v(e)));
                    reinterpret_cast<float4*>(&sm.q[0][0])[tid + 256 * k] = make_float4(v[0], v[1], v[2], v[3]);
                }
            }
            bar_sync(kBarCons, 256);

            {
                const int g = lane >> 3, c = lane & 7;
                const uint32_t lane_off = (uint32_t)((warp * 8 + g) * kRowB + c * 16);
                const float scale = 0.07216878364870322f;
#pragma unroll 1
                for (int j = 0; j < kGH; j++) {
                    const int t = kTK + j;
                    const uint32_t st = t % kStages;
                    float4 q[6];
#pragma unroll
                    for (int i = 0; i < 6; i++) q[i] = *reinterpret_cast<const float4*>(&sm.q[j][(i >> 1) * 64 + c * 8 + (i & 1) * 4]);
                    mbar_wait(full0 + 8 * st, (t / kStages) & 1);
                    const uint32_t a = ring0 + st * kTileB + lane_off;
                    uint4 v[6];
#pragma unroll
                    for (int i = 0; i < 3; i++) { v[i] = lds128(a + i * 128); v[3 + i] = lds128(a + 4 * kRowB + i * 128); }
                    const float s0 = dot8(q[0], q[1], v[0]) + dot8(q[2], q[3], v[1]) + dot8(q[4], q[5], v[2]);
                    const float s1 = dot8(q[0], q[1], v[3]) + dot8(q[2], q[3], v[4]) + dot8(q[4], q[5], v[5]);
                    __syncwarp();
                    if (lane == 0) mbar_arrive(empty0 + 8 * st);
                    float mine = (c & 4) ? s1 : s0;
                    const float other = (c & 4) ? s0 : s1;
                    mine += __shfl_xor_sync(0xffffffffu, other, 4);
                    mine += __shfl_xor_sync(0xffffffffu, mine, 2);
                    mine += __shfl_xor_sync(0xffffffffu, mine, 1);
                    if ((c & 3) == 0) sm.sc[j][warp * 8 + c + g] = bfr(bfr(mine) * scale);
                }
            }
            bar_sync(kBarCons, 256);
            {
                float4 sv = *reinterpret_cast<const float4*>(&sm.sc[0][tid * 4]);
                float m = fmaxf(fmaxf(sv.x, sv.y), fmaxf(sv.z, sv.w));
#pragma unroll
                for (int o = 8; o > 0; o >>= 1) m = fmaxf(m, __shfl_xor_sync(0xffffffffu, m, o));
                sv.x = __expf(sv.x - m); sv.y = __expf(sv.y - m); sv.z = __expf(sv.z - m); sv.w = __expf(sv.w - m);
                *reinterpret_cast<uint2*>(&sm.rowc[tid * 4]) = make_uint2(pack_bf16(sv.x, sv.y), pack_bf16(sv.z, sv.w));
                float l = (sv.x + sv.y) + (sv.z + sv.w);
#pragma unroll
                for (int o = 8; o > 0; o >>= 1) l += __shfl_xor_sync(0xffffffffu, l, o);
                if ((lane & 15) == 0) { sm.stat[(tid >> 4) * 2] = m; sm.stat[(tid >> 4) * 2 + 1] = l; }
            }
        }

        if (warp < 5) {
            const uint32_t* cw = reinterpret_cast<const uint32_t*>(sm.coef);
            int tqp = tq;
            asm volatile("" : "+r"(tqp));
            const bool q0 = tqp == 0, q1 = tqp == 1;
            float4* slot = acc_slot(p.g, (((cta & 1) * 5 + warp) * 8 + mg) * 3 + tq);
            __nv_bfloat16* o = p.out + ((cta & 1) * 5 + warp) * 64 + tq * 24 + mg;
            float d[4][4];
            uint32_t off[4], w0[8][4], w1[8][4];
            float f0, f1, f2;
#pragma unroll
            for (int i = 0; i < 4; i++) off[i] = lk * 128 + ((((2 * i + ((lane >> 3) & 1)) ^ lk) & 7) << 4);
            {
                const uint32_t b0 = cw[48 + tq], b1 = cw[52 + tq], b2 = cw[56 + tq], b3 = cw[60 + tq];
                const float gb = sm.gate[1];
                const uint32_t a = ring0 + (kTD % kStages) * kTileB + warp * kFC * 128;
                mbar_wait(full0 + 8 * (kTD % kStages), (kTD / kStages) & 1);
#pragma unroll
                for (int i = 0; i < 4; i++) {
                    ldsm4t(w0[i], a + off[i]);
                    ldsm4t(w0[4 + i], a + off[i] + (lane < 16 ? 16 : 8) * 128);
                }
#pragma unroll
                for (int i = 0; i < 4; i++) {
                    d[i][0] = d[i][1] = d[i][2] = d[i][3] = 0.f;
                    mma16816(d[i], w0[i], b0, b1);
                    mma16816(d[i], w0[4 + i], b2, b3);
                }
                f0 = gb * fsel(q0, d[0][0], fsel(q1, d[1][2], d[3][0]));
                f1 = gb * fsel(q0, d[0][2], fsel(q1, d[2][0], d[3][2]));
                f2 = gb * fsel(q0, d[1][0], d[2][2]);
            }
#pragma unroll
            for (int i = 0; i < 4; i++) off[i] += ring0 + warp * 32 * 128;
            asm volatile("" : "+r"(off[0]), "+r"(off[1]), "+r"(off[2]), "+r"(off[3]));
            mbar_wait(full0 + 8 * (kTO % kStages), (kTO / kStages) & 1);
#pragma unroll
            for (int i = 0; i < 8; i++) ldsm4t(w0[i], off[i & 3] + (kTO % kStages) * kTileB + (i >> 2) * 2048);
            uint32_t b[12];
            float ga = sm.gate[0];
#pragma unroll
            for (int i = 0; i < 4; i++) d[i][0] = d[i][1] = d[i][2] = d[i][3] = 0.f;
            const bool early = __all_sync(0xffffffffu, mbar_test(s2u(&sm.coef_ready), 0));
            if (early) {
#pragma unroll
                for (int j = 0; j < 12; j++) b[j] = cw[j * 4 + tq];
#pragma unroll
                for (int i = 0; i < 8; i++) mma16816(d[i & 3], w0[i], b[(i >> 2) * 2], b[(i >> 2) * 2 + 1]);
            }
            asm volatile("" : "+l"(slot), "+l"(o), "+f"(ga), "+f"(f0), "+f"(f1), "+f"(f2));
            mbar_wait(full0 + 8 * ((kTO + 1) % kStages), ((kTO + 1) / kStages) & 1);
#pragma unroll
            for (int i = 0; i < 8; i++) ldsm4t(w1[i], off[i & 3] + ((kTO + 1) % kStages) * kTileB + (i >> 2) * 2048);
            if (!early) {
                mbar_wait(s2u(&sm.coef_ready), 0);
#pragma unroll
                for (int j = 0; j < 12; j++) b[j] = cw[j * 4 + tq];
#pragma unroll
                for (int i = 0; i < 8; i++) mma16816(d[i & 3], w0[i], b[(i >> 2) * 2], b[(i >> 2) * 2 + 1]);
            }
#pragma unroll
            for (int i = 0; i < 8; i++) mma16816(d[i & 3], w1[i], b[4 + (i >> 2) * 2], b[5 + (i >> 2) * 2]);
            mbar_wait(full0 + 8 * ((kTO + 2) % kStages), ((kTO + 2) / kStages) & 1);
#pragma unroll
            for (int i = 0; i < 8; i++) ldsm4t(w0[i], off[i & 3] + ((kTO + 2) % kStages) * kTileB + (i >> 2) * 2048);
#pragma unroll
            for (int i = 0; i < 8; i++) mma16816(d[i & 3], w0[i], b[8 + (i >> 2) * 2], b[9 + (i >> 2) * 2]);
            const float v0 = fmaf(ga, fsel(q0, d[0][0], fsel(q1, d[1][2], d[3][0])), f0);
            const float v1 = fmaf(ga, fsel(q0, d[0][2], fsel(q1, d[2][0], d[3][2])), f1);
            const float v2 = fmaf(ga, fsel(q0, d[1][0], d[2][2]), f2);
            if (tqp < 3) {
                const float4 old = atom_add4(slot, v0, v1, v2, 1.0f);
                if (old.w == (float)(kCTAs / 2 - 1)) {
                    st_bf16(o, old.x + v0);
                    st_bf16(o + 8, old.y + v1);
                    if (tqp < 2) st_bf16(o + 16, old.z + v2);
                }
            }
        }
        if (warp < 6) return;
    }

    {
        const int tt = warp == kCW + 1 ? 64 + lane : tid - 192;
        const int half = (cta >> 1) & 1;
        bar_sync(kBarTeam, 96);
        mbar_wait(s2u(&sm.go[1]), 0);
        if (hl >= kGH - kLate) {
            if (tt < kOC / 2) {
                float4* slot = acc_slot(p.g, kSlots + ((cta >> 6) * kLate + hl - (kGH - kLate)) * kOSlots + half * (kOC / 2) + tt);
                float4 r;
                unsigned n = 0;
                do { r = atom_add4(slot, 0.f, 0.f, 0.f, 0.f); if (++n > kSpinLimit) __trap(); } while (r.w != (float)kGrp);
                const int d = (tt >> 4) * 32 + (tt & 1) * 16 + ((tt >> 1) & 7);
                sm.coef[d] = __float2bfloat16_rn(r.x);
                sm.coef[d + 8] = __float2bfloat16_rn(r.y);
            }
        } else {
            const int c = tt % 24, sg = tt / 24;
            const unsigned* const ps[1] = {&p.g->omail[hl][cta0 + sg][half * kOC + c * 4]};
            Chunk r[16];
            mail_gather<16>(ps, 4 * kDh, tag, r);
            float4 acc = make_float4(0.f, 0.f, 0.f, 0.f);
#pragma unroll
            for (int k = 0; k < 16; k++) {
                const float w = sm.wgt[sg + 4 * k];
                acc.x = fmaf(w, r[k].v(0), acc.x); acc.y = fmaf(w, r[k].v(1), acc.y);
                acc.z = fmaf(w, r[k].v(2), acc.z); acc.w = fmaf(w, r[k].v(3), acc.w);
            }
            *reinterpret_cast<float4*>(&sm.part[sg][c * 4]) = acc;
            bar_sync(kBarTeam, 96);
            if (tt < kOC / 2) {
                const float2 a = *reinterpret_cast<const float2*>(&sm.part[0][tt * 2]), b = *reinterpret_cast<const float2*>(&sm.part[1][tt * 2]);
                const float2 e = *reinterpret_cast<const float2*>(&sm.part[2][tt * 2]), f = *reinterpret_cast<const float2*>(&sm.part[3][tt * 2]);
                reinterpret_cast<uint32_t*>(sm.coef)[tt] = pack_bf16((a.x + b.x) + (e.x + f.x), (a.y + b.y) + (e.y + f.y));
            }
        }
        __syncwarp();
        if (tt < 64 && lane == 0) mbar_arrive(s2u(&sm.coef_ready));
    }
}

__device__ float g_fb[2 * kH * kDh + kF];
__device__ __forceinline__ float ldbf(const void* p, size_t i) { return __bfloat162float(reinterpret_cast<const __nv_bfloat16*>(p)[i]); }
__global__ void fb_proj(const void* x, const void* wq, const void* wg, const void* wu) {
    const int n = blockIdx.x * blockDim.x + threadIdx.x;
    if (n < kH * kDh) {
        float a = 0.f;
        for (int k = 0; k < kD; k++) a = fmaf(ldbf(x, k), ldbf(wq, (size_t)k * kH * kDh + n), a);
        g_fb[n] = bfr(a);
    } else if (n < kH * kDh + kF) {
        const int f = n - kH * kDh;
        float a = 0.f, b = 0.f;
        for (int k = 0; k < kD; k++) { a = fmaf(ldbf(x, k), ldbf(wg, (size_t)k * kF + f), a); b = fmaf(ldbf(x, k), ldbf(wu, (size_t)k * kF + f), b); }
        a = bfr(a);
        g_fb[2 * kH * kDh + f] = bfr((a > 0.f ? a : a * 0.f) * bfr(b));
    }
}
__global__ void fb_attn(const void* kc, const void* vc) {
    __shared__ float sc[kW], red[kDh];
    const int h = blockIdx.x, t = threadIdx.x;
    const size_t base = ((size_t)h * kSk + kSk - kW) * kDh;
    float m = -INFINITY, l = 0.f, o = 0.f;
    for (int k = t; k < kW; k += kDh) {
        float a = 0.f;
        for (int d = 0; d < kDh; d++) a = fmaf(g_fb[h * kDh + d], ldbf(kc, base + (size_t)k * kDh + d), a);
        sc[k] = bfr(bfr(a) * 0.07216878364870322f);
        m = fmaxf(m, sc[k]);
    }
    red[t] = m;
    __syncthreads();
    for (int i = 0; i < kDh; i++) m = fmaxf(m, red[i]);
    for (int k = 0; k < kW; k++) {
        const float e = __expf(sc[k] - m);
        l += e;
        o = fmaf(e, ldbf(vc, base + (size_t)k * kDh + t), o);
    }
    g_fb[kH * kDh + h * kDh + t] = bfr(o / l);
}
__global__ void fb_out(const void* x, const void* gw, const void* wo, const void* wd, __nv_bfloat16* out) {
    const int n = blockIdx.x * blockDim.x + threadIdx.x;
    float z = 0.f, a = 0.f, b = 0.f;
    for (int k = 0; k < kD; k++) z += bfr(ldbf(x, k) * ldbf(gw, k));
    const float g = bfr(1.0f / (1.0f + __expf(-bfr(z))));
    for (int k = 0; k < kH * kDh; k++) a = fmaf(g_fb[kH * kDh + k], ldbf(wo, (size_t)k * kD + n), a);
    for (int k = 0; k < kF; k++) b = fmaf(g_fb[2 * kH * kDh + k], ldbf(wd, (size_t)k * kD + n), b);
    out[n] = __float2bfloat16_rn(g * a + bfr(1.0f - g) * b);
}

typedef CUresult (*EncodeFn)(CUtensorMap*, CUtensorMapDataType, cuuint32_t, void*, const cuuint64_t*, const cuuint64_t*,
                             const cuuint32_t*, const cuuint32_t*, CUtensorMapInterleave, CUtensorMapSwizzle,
                             CUtensorMapL2promotion, CUtensorMapFloatOOBfill);

void make_map(EncodeFn fn, CUtensorMap* m, void* base, int rows, int cols, int box_rows) {
    const cuuint64_t dims[3] = {64, (cuuint64_t)(cols / 64), (cuuint64_t)rows};
    const cuuint64_t strides[2] = {128, (cuuint64_t)cols * 2};
    const cuuint32_t box[3] = {64, 3, (cuuint32_t)box_rows};
    const cuuint32_t estr[3] = {1, 1, 1};
    fn(m, CU_TENSOR_MAP_DATA_TYPE_BFLOAT16, 3, base, dims, strides, box, estr, CU_TENSOR_MAP_INTERLEAVE_NONE,
       CU_TENSOR_MAP_SWIZZLE_128B, CU_TENSOR_MAP_L2_PROMOTION_NONE, CU_TENSOR_MAP_FLOAT_OOB_FILL_NONE);
}
void make_map_out(EncodeFn fn, CUtensorMap* m, void* base, int rows, int box_rows) {
    const cuuint64_t dims[3] = {64, (cuuint64_t)rows, (cuuint64_t)(kD / 64)};
    const cuuint64_t strides[2] = {(cuuint64_t)kOutRowB, 128};
    const cuuint32_t box[3] = {64, (cuuint32_t)box_rows, 5};
    const cuuint32_t estr[3] = {1, 1, 1};
    fn(m, CU_TENSOR_MAP_DATA_TYPE_BFLOAT16, 3, base, dims, strides, box, estr, CU_TENSOR_MAP_INTERLEAVE_NONE,
       CU_TENSOR_MAP_SWIZZLE_128B, CU_TENSOR_MAP_L2_PROMOTION_NONE, CU_TENSOR_MAP_FLOAT_OOB_FILL_NONE);
}

}

extern "C" void kernel_launch(void* const* d_in, const int* in_sizes, int n_in, void* d_out, int out_size) {
    (void)in_sizes; (void)n_in; (void)out_size;
    static EncodeFn encode = nullptr;
    static void* scratch = nullptr;
    static int resident = -1;
    if (resident < 0) {
        cudaGetSymbolAddress(&scratch, g_scratch);
        void* fn = nullptr;
        cudaDriverEntryPointQueryResult qr;
        cudaGetDriverEntryPoint("cuTensorMapEncodeTiled", &fn, cudaEnableDefault, &qr);
        encode = (EncodeFn)fn;
        cudaFuncSetAttribute(fused_decode_kernel, cudaFuncAttributeMaxDynamicSharedMemorySize, (int)sizeof(Smem));
        int dev = 0, sms = 0, per_sm = 0;
        cudaGetDevice(&dev);
        cudaDeviceGetAttribute(&sms, cudaDevAttrMultiProcessorCount, dev);
        cudaOccupancyMaxActiveBlocksPerMultiprocessor(&per_sm, fused_decode_kernel, kThreads, sizeof(Smem));
        resident = sms * per_sm;
    }
    if (resident < kCTAs || !encode) {
        fb_proj<<<(kH * kDh + kF) / 128, 128, 0, cudaStreamPerThread>>>(d_in[0], d_in[3], d_in[6], d_in[7]);
        fb_attn<<<kH, kDh, 0, cudaStreamPerThread>>>(d_in[1], d_in[2]);
        fb_out<<<kD / 32, 32, 0, cudaStreamPerThread>>>(d_in[0], d_in[9], d_in[4], d_in[8], (__nv_bfloat16*)d_out);
        return;
    }
    Params p;
    p.x = (const __nv_bfloat16*)d_in[0];
    p.k = (const unsigned char*)d_in[1];
    p.gate_w = (const __nv_bfloat16*)d_in[9];
    p.out = (__nv_bfloat16*)d_out;
    p.g = (Scratch*)scratch;
    make_map(encode, &p.tq, d_in[3], kD, kH * kDh, 32);
    make_map(encode, &p.tg, d_in[6], kD, kF, 16);
    make_map(encode, &p.tu, d_in[7], kD, kF, 16);
    make_map(encode, &p.tv, d_in[2], kH * kSk, kDh, kTileKeys);
    make_map_out(encode, &p.td, d_in[8], kF, kFC);
    make_map_out(encode, &p.to, d_in[4], kH * kDh, 32);
    fused_decode_kernel<<<kCTAs, kThreads, sizeof(Smem), cudaStreamPerThread>>>((const unsigned char*)d_in[3], p);
}
```

```cpp
#include <cuda_runtime.h>
#include <cuda_bf16.h>
#include <cuda.h>
#include <math.h>
#include <stdint.h>

namespace {

constexpr int kD = 640;
constexpr int kH = 32;
constexpr int kDh = 192;
constexpr int kSk = 32768;
constexpr int kW = 4096;
constexpr int kF = 1536;
constexpr int kCTAs = 128;
constexpr int kGrp = 64;
constexpr int kGH = kH * kGrp / kCTAs;
constexpr int kCW = 8;
constexpr int kThreads = kCW * 32 + 64;
constexpr int kTileKeys = kW / kGrp;
constexpr int kRowB = kDh * 2;
constexpr int kTileB = kTileKeys * kRowB;
constexpr int kStages = 8;
constexpr int kOutRowB = kD * 2;
constexpr int kFC = 2 * kF / kCTAs;
constexpr int kOC = 2 * kH * kDh / kCTAs;
constexpr int kXR = kD / 4;
constexpr int kFR = kD / 8;
constexpr int kTQ = 0;
constexpr int kTK = 3;
constexpr int kTF = kTK + kGH;
constexpr int kTV = kTF + 2;
constexpr int kTD = kTV + kGH;
constexpr int kTO = kTD + 1;
constexpr int kNumTiles = kTO + 3;
constexpr int kSlots = 240;
constexpr int kLate = 4;
constexpr int kOSlots = kDh / 2;
constexpr int kAccSlots = kSlots + 2 * kLate * kOSlots;
constexpr unsigned kSpinLimit = 1u << 24;
static_assert(kTD - kLate + kStages > kNumTiles - 1, "the producer must be able to finish before the late V tiles are consumed");

constexpr uint32_t kWindow = 71000;
constexpr int kBalStart = 8;
constexpr int kLead0 = 16, kLead1 = 72, kLead2 = 128;
constexpr int kMile = 576, kMileLate = 384;
constexpr unsigned kMileQ = 400;

constexpr int kCbQ = kGH * kTileKeys, kCbF = kCbQ + kXR, kCbLen = kCbF + kFR;

struct Smem {
    alignas(1024) unsigned char ring[kStages][kTileB];
    alignas(16) float q[kGH][kDh];
    alignas(16) float sc[kGH][kTileKeys];
    alignas(16) __nv_bfloat16 rowc[kCbLen];
    alignas(16) __nv_bfloat16 coef[128];
    alignas(16) float part[4][kOC];
    float wgt[kGrp];
    float lscale[kLate];
    float stat[2 * kGH];
    float gate[2];
    unsigned tag;
    alignas(8) unsigned long long full[kStages];
    alignas(8) unsigned long long empty[kStages];
    alignas(8) unsigned long long coef_ready;
    alignas(8) unsigned long long go[2];
};

struct Scratch {
    alignas(256) unsigned epoch;
    alignas(256) unsigned accflag;
    alignas(256) unsigned prog;
    alignas(256) float4 acc[kAccSlots * 4];
    alignas(256) unsigned stat[kCTAs][2 * kGH];
    alignas(256) unsigned qmail[kCTAs][kDh];
    alignas(256) unsigned fmail[kCTAs][kDh];
    alignas(256) unsigned omail[kGH - kLate][kCTAs][kDh];
};
__device__ Scratch g_scratch;

__device__ __forceinline__ uint32_t s2u(const void* p) { return (uint32_t)__cvta_generic_to_shared(p); }

__device__ __forceinline__ void mbar_init(uint32_t bar, uint32_t cnt) {
    asm volatile("mbarrier.init.shared::cta.b64 [%0], %1;" ::"r"(bar), "r"(cnt) : "memory");
}
__device__ __forceinline__ void mbar_expect_tx(uint32_t bar, uint32_t bytes) {
    asm volatile("mbarrier.arrive.expect_tx.shared::cta.b64 _, [%0], %1;" ::"r"(bar), "r"(bytes) : "memory");
}
__device__ __forceinline__ void mbar_arrive(uint32_t bar, uint32_t cnt = 1) {
    asm volatile("mbarrier.arrive.shared::cta.b64 _, [%0], %1;" ::"r"(bar), "r"(cnt) : "memory");
}
__device__ __forceinline__ void mbar_wait(uint32_t bar, uint32_t parity) {
    asm volatile("{\n.reg .pred p;\n.reg .u32 n;\nmov.u32 n, 0;\n"
                 "WL:\nmbarrier.try_wait.parity.shared::cta.b64 p, [%0], %1;\n@p bra WD;\n"
                 "add.u32 n, n, 1;\nsetp.lt.u32 p, n, %2;\n@p bra WL;\ntrap;\nWD:\n}"
                 ::"r"(bar), "r"(parity), "n"(kSpinLimit) : "memory");
}
__device__ __forceinline__ bool mbar_test(uint32_t bar, uint32_t parity) {
    uint32_t ok;
    asm volatile("{\n.reg .pred p;\nmbarrier.test_wait.parity.shared::cta.b64 p, [%1], %2;\nselp.u32 %0, 1, 0, p;\n}"
                 : "=r"(ok) : "r"(bar), "r"(parity) : "memory");
    return ok != 0;
}
__device__ __forceinline__ void bulk_g2s(uint32_t dst, const void* src, uint32_t bytes, uint32_t bar, uint64_t pol) {
    asm volatile("cp.async.bulk.shared::cluster.global.mbarrier::complete_tx::bytes.L2::cache_hint [%0], [%1], %2, [%3], %4;"
                 ::"r"(dst), "l"(src), "r"(bytes), "r"(bar), "l"(pol) : "memory");
}
__device__ __forceinline__ void tma_3d(uint32_t dst, const CUtensorMap* map, int c1, int c2, uint32_t bar, uint64_t pol) {
    asm volatile("cp.async.bulk.tensor.3d.shared::cluster.global.mbarrier::complete_tx::bytes.L2::cache_hint [%0], [%1, {%4, %3, %6}], [%2], %5;"
                 ::"r"(dst), "l"(map), "r"(bar), "r"(c1), "r"(0), "l"(pol), "r"(c2) : "memory");
}
__device__ __forceinline__ void ldsm4t(uint32_t (&r)[4], uint32_t a) {
    asm volatile("ldmatrix.sync.aligned.m8n8.x4.trans.shared.b16 {%0,%1,%2,%3}, [%4];"
                 : "=r"(r[0]), "=r"(r[1]), "=r"(r[2]), "=r"(r[3]) : "r"(a));
}
__device__ __forceinline__ void mma16816(float (&d)[4], const uint32_t (&a)[4], uint32_t b0, uint32_t b1) {
    asm volatile("mma.sync.aligned.m16n8k16.row.col.f32.bf16.bf16.f32 {%0,%1,%2,%3}, {%4,%5,%6,%7}, {%8,%9}, {%0,%1,%2,%3};"
                 : "+f"(d[0]), "+f"(d[1]), "+f"(d[2]), "+f"(d[3]) : "r"(a[0]), "r"(a[1]), "r"(a[2]), "r"(a[3]), "r"(b0), "r"(b1));
}
__device__ __forceinline__ uint4 ldg128(const void* p) {
    uint4 v;
    asm volatile("ld.global.nc.v4.u32 {%0,%1,%2,%3}, [%4];" : "=r"(v.x), "=r"(v.y), "=r"(v.z), "=r"(v.w) : "l"(p));
    return v;
}
__device__ __forceinline__ uint4 lds128(uint32_t a) {
    uint4 v;
    asm volatile("ld.shared.v4.u32 {%0,%1,%2,%3}, [%4];" : "=r"(v.x), "=r"(v.y), "=r"(v.z), "=r"(v.w) : "r"(a));
    return v;
}

__device__ __forceinline__ void word_st(unsigned* p, float v, unsigned tag) {
    asm volatile("st.relaxed.gpu.global.u32 [%0], %1;" ::"l"(p), "r"((__float_as_uint(v) & ~3u) | tag) : "memory");
}
__device__ __forceinline__ float word_val(unsigned w) { return __uint_as_float(w & ~3u); }
struct Chunk {
    unsigned w[4];
    __device__ __forceinline__ float v(int i) const { return word_val(w[i]); }
};
__device__ __forceinline__ unsigned mail_poll(const unsigned* p) {
    unsigned r;
    asm volatile("atom.relaxed.gpu.global.or.b32 %0, [%1], 0;" : "=r"(r) : "l"(p) : "memory");
    return r;
}
template <int N, int NP = N>
__device__ __forceinline__ void mail_gather(const unsigned* const (&p)[N / NP], int stride, unsigned tag, Chunk (&r)[N]) {
#pragma unroll
    for (int i = 0; i < N; i++) {
        asm volatile("ld.relaxed.gpu.global.v4.u32 {%0,%1,%2,%3}, [%4];"
                     : "=r"(r[i].w[0]), "=r"(r[i].w[1]), "=r"(r[i].w[2]), "=r"(r[i].w[3])
                     : "l"(p[i / NP] + (i % NP) * stride) : "memory");
    }
    unsigned n = 0;
#pragma unroll 1
    while (true) {
        unsigned bad = 0;
#pragma unroll
        for (int i = 0; i < N; i++)
            bad |= (((r[i].w[0] ^ tag) | (r[i].w[1] ^ tag) | (r[i].w[2] ^ tag) | (r[i].w[3] ^ tag)) & 3u) ? 1u << i : 0u;
        bad = __reduce_or_sync(0xffffffffu, bad);
        if (bad == 0) break;
        __nanosleep(200);
#pragma unroll
        for (int i = 0; i < N; i++) {
            if (bad >> i & 1) {
#pragma unroll
                for (int e = 0; e < 4; e++) r[i].w[e] = mail_poll(p[i / NP] + (i % NP) * stride + e);
            }
        }
        if (++n > kSpinLimit) __trap();
    }
}
__device__ __forceinline__ void word_wait(const unsigned* p, unsigned tag) {
    unsigned n = 0;
    while ((mail_poll(p) ^ tag) & 3u) { __nanosleep(100); if (++n > kSpinLimit) __trap(); }
}

__device__ __forceinline__ float4 atom_add4(float4* p, float a, float b, float c, float d) {
    float4 r;
    asm volatile("atom.relaxed.gpu.global.add.v4.f32 {%0,%1,%2,%3}, [%4], {%5,%6,%7,%8};"
                 : "=f"(r.x), "=f"(r.y), "=f"(r.z), "=f"(r.w) : "l"(p), "f"(a), "f"(b), "f"(c), "f"(d) : "memory");
    return r;
}
__device__ __forceinline__ float4* acc_slot(Scratch* g, int i) { return &g->acc[(i >> 2) * 16 + (i & 3)]; }

enum { kBarCons = 1, kBarStart = 2, kBarStats = 3, kBarScalars = 4, kBarTeam = 5, kBarInit = 6 };
__device__ __forceinline__ void bar_sync(int id, int n) { asm volatile("barrier.sync %0, %1;" ::"r"(id), "r"(n) : "memory"); }
__device__ __forceinline__ void bar_arrive(int id, int n) { asm volatile("barrier.arrive %0, %1;" ::"r"(id), "r"(n) : "memory"); }

__device__ __forceinline__ void st_bf16(__nv_bfloat16* p, float v) {
    asm volatile("st.global.u16 [%0], %1;" ::"l"(p), "h"(__bfloat16_as_ushort(__float2bfloat16_rn(v))) : "memory");
}
__device__ __forceinline__ float fsel(bool c, float a, float b) {
    float r;
    asm("{\n.reg .pred p;\nsetp.ne.u32 p, %3, 0;\nselp.f32 %0, %1, %2, p;\n}" : "=f"(r) : "f"(a), "f"(b), "r"((unsigned)c));
    return r;
}
__device__ __forceinline__ float bf_lo(uint32_t w) { return __uint_as_float(w << 16); }
__device__ __forceinline__ float bf_hi(uint32_t w) { return __uint_as_float(w & 0xffff0000u); }
__device__ __forceinline__ float bfr(float v) { return __bfloat162float(__float2bfloat16_rn(v)); }
__device__ __forceinline__ uint32_t pack_bf16(float lo, float hi) {
    const __nv_bfloat162 v = __floats2bfloat162_rn(lo, hi);
    return *reinterpret_cast<const uint32_t*>(&v);
}
__device__ __forceinline__ float dot8(const float4& qa, const float4& qb, const uint4& v) {
    float a = qa.x * bf_lo(v.x), b = qa.y * bf_hi(v.x);
    a = fmaf(qa.z, bf_lo(v.y), a); b = fmaf(qa.w, bf_hi(v.y), b);
    a = fmaf(qb.x, bf_lo(v.z), a); b = fmaf(qb.y, bf_hi(v.z), b);
    a = fmaf(qb.z, bf_lo(v.w), a); b = fmaf(qb.w, bf_hi(v.w), b);
    return a + b;
}
__device__ __forceinline__ bool elect_one() {
    uint32_t ok;
    asm volatile("{\n.reg .pred p;\nelect.sync _|p, 0xffffffff;\nselp.u32 %0, 1, 0, p;\n}" : "=r"(ok));
    return ok != 0;
}

__host__ __device__ constexpr uint32_t tile_bytes(int t) {
    return (t == kTQ + 2 || t == kTF + 1) ? 32 * kRowB
         : t == kTF ? 48 * kRowB
         : t == kTD ? kFC * kOutRowB / 2
         : t >= kTO ? 32 * kOutRowB / 2 : kTileB;
}
constexpr uint64_t pack_back(int first) {
    uint64_t r = 0;
    for (int t = first; t < first + 21 && t < kNumTiles; t++) {
        uint32_t sum = 0;
        int j = t;
        for (; j >= 0; j--) { sum += tile_bytes(j); if (sum > kWindow) break; }
        r |= (uint64_t)(t - j > 5 ? 5 : t - j) << (3 * (t - first));
    }
    return r;
}
constexpr uint64_t kBackA = pack_back(0), kBackB = pack_back(21);
__device__ __forceinline__ int look_back(int t) {
    return (int)(((t < 21 ? kBackA : kBackB) >> (3 * (t < 21 ? t : t - 21))) & 7);
}

struct Params {
    const __nv_bfloat16* x;
    const unsigned char* k;
    const __nv_bfloat16* gate_w;
    __nv_bfloat16* out;
    Scratch* g;
    CUtensorMap tq;
    CUtensorMap tg;
    CUtensorMap tu;
    CUtensorMap tv;
    CUtensorMap td;
    CUtensorMap to;
};

__global__ void __launch_bounds__(kThreads, 1)
fused_decode_kernel(const unsigned char* __restrict__ wq, const __grid_constant__ Params p) {
    if (threadIdx.x == 0)
        asm volatile("cp.async.bulk.prefetch.L2.global [%0], %1;"
                     ::"l"(wq + (size_t)((blockIdx.x >> 5) * kXR + (blockIdx.x & 31)) * (kH * kRowB)), "n"(kH * kRowB) : "memory");
    extern __shared__ __align__(1024) unsigned char smem_raw[];
    Smem& sm = *reinterpret_cast<Smem*>(smem_raw);
    const int tid = threadIdx.x;
    const int lane = tid & 31;
    const int warp = tid >> 5;
    const int cta = blockIdx.x;
    const int cta0 = cta & ~(kGrp - 1);
    const int hl = (cta >> 2) & (kGH - 1);
    const uint32_t ring0 = s2u(&sm.ring[0][0]);
    const uint32_t full0 = s2u(&sm.full[0]);
    const uint32_t empty0 = s2u(&sm.empty[0]);

    uint64_t pol;
    asm volatile("createpolicy.fractional.L2::evict_first.b64 %0, 1.0;" : "=l"(pol));
    if (warp == kCW && elect_one()) {
#pragma unroll
        for (int i = 0; i < kTK; i++) mbar_init(full0 + 8 * i, 1);
        asm volatile("fence.mbarrier_init.release.cluster;" ::: "memory");
#pragma unroll
        for (int i = 0; i < kTK; i++) {
            const int row = (cta & 3) * kXR + i * 64;
            mbar_expect_tx(full0 + 8 * i, tile_bytes(i));
            tma_3d(ring0 + i * kTileB, &p.tq, (cta >> 2) * 3, row, full0 + 8 * i, pol);
            if (i < 2) tma_3d(ring0 + i * kTileB + 32 * kRowB, &p.tq, (cta >> 2) * 3, row + 32, full0 + 8 * i, pol);
        }
    }
    __syncwarp();

    if (warp == kCW) {
        const bool leader = elect_one();
        bar_sync(kBarInit, 64);
        bar_arrive(kBarStart, kThreads);
        const int key0 = (cta >> 6) * kGH * kSk + (kSk - kW) + (cta & (kGrp - 1)) * kTileKeys;
        const unsigned char* src = p.k + (size_t)key0 * kRowB;
        constexpr unsigned kProgMax = (kNumTiles - kTK) * kCTAs - 1;
        unsigned prog = 0;
        constexpr int kNever = 1 << 30;
        int mile0 = (kTV - 1 - kTK) * kCTAs + kMile, mile1 = (kTV + hl - kTK) * kCTAs + (hl < kGH - kLate ? kMile : kMileLate);
#pragma unroll 1
        for (int t = kTK; t < kNumTiles; t++) {
            const uint32_t st = t % kStages;
            const uint32_t dst = ring0 + st * kTileB, bar = full0 + 8 * st;
            if (t >= kStages) mbar_wait(empty0 + 8 * st, ((t / kStages) - 1) & 1);
            if (leader) mbar_expect_tx(bar, tile_bytes(t));
            int need = t - look_back(t);
            if (t >= kBalStart) {
                const int gp = (int)__shfl_sync(0xffffffffu, prog, 0);
                const int lead = (t - kTK) * kCTAs - gp;
                need += (lead > kLead2) - (lead <= kLead1) - (lead <= kLead0);
                const int seen = t == kNumTiles - 1 ? kNever - 1 : gp;
                if (seen >= mile0) { mile0 = kNever; if (leader) mbar_arrive(s2u(&sm.go[0])); }
                if (seen >= mile1) { mile1 = kNever; if (leader) mbar_arrive(s2u(&sm.go[1])); }
            }
            if (need >= 0) mbar_wait(full0 + 8 * (need % kStages), (need / kStages) & 1);
            if (leader) {
                if (t < kTF) {
                    bulk_g2s(dst, src, kTileB, bar, pol);
                } else if (t < kTV) {
                    const CUtensorMap* m = cta < 64 ? &p.tg : &p.tu;
                    const int row = (cta & 7) * kFR + (t - kTF) * 48, blk = ((cta >> 3) & 7) * 3;
                    tma_3d(dst, m, blk, row, bar, pol);
                    tma_3d(dst + 16 * kRowB, m, blk, row + 16, bar, pol);
                    if (t == kTF) tma_3d(dst + 32 * kRowB, m, blk, row + 32, bar, pol);
                } else if (t < kTD) {
                    tma_3d(dst, &p.tv, 0, key0 + (t - kTV) * kSk, bar, pol);
                } else {
                    tma_3d(dst, t == kTD ? &p.td : &p.to, t == kTD ? (cta >> 1) * kFC : (cta >> 1) * kOC + (t - kTO) * 32,
                           (cta & 1) * 5, bar, pol);
                }
            }
            if (leader && t == 12) {
                asm volatile("prefetch.tensormap [%0];" ::"l"(cta < 64 ? &p.tg : &p.tu) : "memory");
                asm volatile("prefetch.tensormap [%0];" ::"l"(&p.tv) : "memory");
                asm volatile("prefetch.tensormap [%0];" ::"l"(&p.td) : "memory");
                asm volatile("prefetch.tensormap [%0];" ::"l"(&p.to) : "memory");
            }
            src += (size_t)kSk * kRowB;
            if (lane == 0) {
                if (t + 1 >= kBalStart)
                    asm volatile("atom.relaxed.gpu.global.inc.u32 %0, [%1], %2;" : "=r"(prog) : "l"(&p.g->prog), "n"(kProgMax) : "memory");
                else
                    asm volatile("red.relaxed.gpu.global.inc.u32 [%0], %1;" ::"l"(&p.g->prog), "n"(kProgMax) : "memory");
            }
        }
        if (lane == 0 && prog == kProgMax) p.g->epoch = sm.tag;
        return;
    }

    unsigned tag;
    if (warp == kCW + 1) {
        if (elect_one()) {
#pragma unroll
            for (int i = 0; i < kStages; i++) { if (i >= kTK) mbar_init(full0 + 8 * i, 1); mbar_init(empty0 + 8 * i, kCW); }
            mbar_init(s2u(&sm.coef_ready), 2);
            mbar_init(s2u(&sm.go[0]), 1);
            mbar_init(s2u(&sm.go[1]), 1);
            asm volatile("fence.mbarrier_init.release.cluster;" ::: "memory");
        }
        __syncwarp();
        bar_arrive(kBarInit, 64);
        unsigned e = 0;
        if (lane == 31) asm volatile("ld.relaxed.gpu.global.u32 %0, [%1];" : "=r"(e) : "l"(&p.g->epoch) : "memory");
        if (lane < 30) {
            const uint4 v = ldg128(p.x + (lane < 20 ? (cta & 3) * kXR + lane * 8 : (cta & 7) * kFR + (lane - 20) * 8));
            *reinterpret_cast<uint4*>(&sm.rowc[kCbQ + lane * 8]) = v;
        }
        tag = __shfl_sync(0xffffffffu, e, 31) % 3u + 1u;
        if (lane == 0) sm.tag = tag;
        bar_arrive(kBarStart, kThreads);
        __nanosleep(3000);
        if (cta == 0) {
            for (int i = lane; i < kAccSlots; i += 32) *acc_slot(p.g, i) = make_float4(0.f, 0.f, 0.f, 0.f);
            __threadfence();
            __syncwarp();
            if (lane == 0) { __threadfence(); word_st(&p.g->accflag, 0.f, tag); }
        }
        {
            float z = 0.f;
#pragma unroll 1
            for (int j = lane; j < kD / 8; j += 32) {
                const uint4 gx = ldg128(p.x + j * 8), gw = ldg128(p.gate_w + j * 8);
                z += bfr(bf_lo(gx.x) * bf_lo(gw.x)) + bfr(bf_hi(gx.x) * bf_hi(gw.x));
                z += bfr(bf_lo(gx.y) * bf_lo(gw.y)) + bfr(bf_hi(gx.y) * bf_hi(gw.y));
                z += bfr(bf_lo(gx.z) * bf_lo(gw.z)) + bfr(bf_hi(gx.z) * bf_hi(gw.z));
                z += bfr(bf_lo(gx.w) * bf_lo(gw.w)) + bfr(bf_hi(gx.w) * bf_hi(gw.w));
            }
#pragma unroll
            for (int o = 16; o > 0; o >>= 1) z += __shfl_xor_sync(0xffffffffu, z, o);
            const float gate = bfr(1.0f / (1.0f + __expf(-bfr(z))));
            if (lane == 0) { sm.gate[0] = gate; sm.gate[1] = bfr(1.0f - gate); }
            if (lane < 8) sm.coef[kOC + kFC + lane] = __float2bfloat16_rn(0.f);
        }
        __nanosleep(2000);
        if (lane == 0) {
            word_wait(&p.g->accflag, tag);
            __threadfence();
        }
        __syncwarp();
        bar_sync(kBarStats, 288);
        word_st(&p.g->stat[cta][lane], sm.stat[lane], tag);
        mbar_wait(s2u(&sm.go[0]), 0);
        {
            const int mtx = lane >> 4, rb = (lane >> 1) & 7, half = lane & 1;
            const unsigned* sa = p.g->stat[cta0 + lane];
            const unsigned* sb = p.g->stat[cta0 + 32 + lane];
            const unsigned* fm = &p.g->fmail[(mtx * 8 + (cta >> 4)) * 8 + rb][((cta >> 1) & 7) * kFC + half * 12];
            const unsigned* const ps[9] = {sa + (hl >> 1) * 4, sb + (hl >> 1) * 4, sa + 24, sb + 24, sa + 28, sb + 28, fm, fm + 4, fm + 8};
            Chunk r[9];
            mail_gather<9, 1>(ps, 0, tag, r);
#pragma unroll 1
            for (int i = -1; i < kLate; i++) {
                const int hd = i < 0 ? hl : kGH - kLate + i;
                const Chunk a = i < 0 ? r[0] : hd < 14 ? r[2] : r[4], b = i < 0 ? r[1] : hd < 14 ? r[3] : r[5];
                const float m0 = hd & 1 ? a.v(2) : a.v(0), l0 = hd & 1 ? a.v(3) : a.v(1);
                const float m1 = hd & 1 ? b.v(2) : b.v(0), l1 = hd & 1 ? b.v(3) : b.v(1);
                float M = fmaxf(m0, m1);
#pragma unroll
                for (int o = 16; o > 0; o >>= 1) M = fmaxf(M, __shfl_xor_sync(0xffffffffu, M, o));
                const float w0 = __expf(m0 - M), w1 = __expf(m1 - M);
                float L = w0 * l0 + w1 * l1;
#pragma unroll
                for (int o = 16; o > 0; o >>= 1) L += __shfl_xor_sync(0xffffffffu, L, o);
                if (i < 0) { sm.wgt[lane] = w0 / L; sm.wgt[lane + 32] = w1 / L; }
                else if (lane == (cta & 31)) sm.lscale[i] = ((cta & 32) ? w1 : w0) / L;
            }
#pragma unroll
            for (int j = 0; j < 12; j++) {
                float v = r[6 + (j >> 2)].v(j & 3);
                v += __shfl_xor_sync(0xffffffffu, v, 2);
                v += __shfl_xor_sync(0xffffffffu, v, 4);
                v += __shfl_xor_sync(0xffffffffu, v, 8);
                const float gt = bfr(v);
                const float up = __shfl_xor_sync(0xffffffffu, gt, 16);
                if (lane < 2) sm.coef[kOC + half * 12 + j] = __float2bfloat16_rn((gt > 0.f ? gt : gt * 0.f) * up);
            }
        }
        bar_arrive(kBarScalars, 224);
    } else {
        bar_sync(kBarStart, kThreads);
        tag = sm.tag;

        const int mg = lane >> 2, tq = lane & 3;
        const int lk = (lane & 7) + ((lane >> 4) << 3);
        uint32_t voff[2];
#pragma unroll
        for (int i = 0; i < 2; i++) {
            const int line = lk * 3 + (warp >> 1);
            voff[i] = line * 128 + (((((warp & 1) * 4 + 2 * i + ((lane >> 3) & 1)) ^ line) & 7) << 4);
        }
#pragma unroll 1
        for (int pass = 0; pass < 3; pass++) {
            if (warp < 6) {
                const int t0 = pass == 0 ? kTQ : (pass == 1 ? kTF : kTV);
                const int t1 = pass == 0 ? kTK : (pass == 1 ? kTV : kTD);
                const uint32_t* cf = reinterpret_cast<const uint32_t*>(&sm.rowc[pass == 0 ? kCbQ : (pass == 1 ? kCbF : 0)]) + tq;
                float d[4][4];
#pragma unroll
                for (int i = 0; i < 4; i++) d[i][0] = d[i][1] = d[i][2] = d[i][3] = 0.f;
#pragma unroll 1
                for (int t = t0; t < t1; t++) {
                    const uint32_t st = t % kStages;
                    const int nk = tile_bytes(t) / (16 * kRowB);
                    if (t == kTD - kLate) bar_sync(kBarScalars, 224);
                    uint32_t b[8];
#pragma unroll
                    for (int j = 0; j < 8; j++) b[j] = cf[j * 4];
                    cf += nk * 8;
                    const bool late = t >= kTD - kLate;
                    const float ls = sm.lscale[late ? t - (kTD - kLate) : 0];
                    void* dst = late ? (void*)acc_slot(p.g, kSlots + ((cta >> 6) * kLate + t - (kTD - kLate)) * kOSlots + warp * 16 + mg * 2 + (tq >> 1))
                                     : (void*)((t < kTK ? p.g->qmail[cta] : t < kTV ? p.g->fmail[cta] : p.g->omail[t - kTV][cta]) + warp * 32 + tq * 8 + mg);
                    mbar_wait(full0 + 8 * st, (t / kStages) & 1);
                    const uint32_t a = ring0 + st * kTileB;
                    uint32_t w[8][4];
#pragma unroll
                    for (int j = 0; j < 4; j++) ldsm4t(w[j], a + voff[j & 1] + (j >> 1) * (16 * kRowB));
                    if (nk > 2) {
                        ldsm4t(w[4], a + voff[0] + 2 * (16 * kRowB));
                        ldsm4t(w[5], a + voff[1] + 2 * (16 * kRowB));
                    }
                    if (nk > 3) {
                        ldsm4t(w[6], a + voff[0] + 3 * (16 * kRowB));
                        ldsm4t(w[7], a + voff[1] + 3 * (16 * kRowB));
                    }
#pragma unroll
                    for (int j = 0; j < 4; j++) mma16816(d[j], w[j], b[(j >> 1) * 2], b[(j >> 1) * 2 + 1]);
                    if (nk > 2) { mma16816(d[0], w[4], b[4], b[5]); mma16816(d[1], w[5], b[4], b[5]); }
                    if (nk > 3) { mma16816(d[2], w[6], b[6], b[7]); mma16816(d[3], w[7], b[6], b[7]); }
                    if (pass == 2 || t == t1 - 1) {
                        const float c0 = fsel(tq & 2, d[1][0] + d[3][0], d[0][0] + d[2][0]);
                        const float c8 = fsel(tq & 2, d[1][2] + d[3][2], d[0][2] + d[2][2]);
                        if (!late) word_st((unsigned*)dst, fsel(tq & 1, c8, c0), tag);
                        else if (!(tq & 1))
                            asm volatile("red.relaxed.gpu.global.add.v4.f32 [%0], {%1,%2,%3,%4};"
                                         ::"l"(dst), "f"(c0 * ls), "f"(c8 * ls), "f"(0.f), "f"(1.f) : "memory");
#pragma unroll
                        for (int i = 0; i < 4; i++) d[i][0] = d[i][1] = d[i][2] = d[i][3] = 0.f;
                    }
                    __syncwarp();
                    if (lane == 0) mbar_arrive(empty0 + 8 * st, warp < 2 ? 2 : 1);
                }
            }
            if (pass == 1) bar_sync(kBarStats, 288);
            if (pass != 0) continue;

            if (tid == kDh) {
                mbar_wait(full0 + 8 * kTK, 0);
                for (int n = 0; n < 64 && mail_poll(&p.g->prog) < kMileQ; n++) __nanosleep(150);
            }
            bar_sync(kBarCons, 256);
            {
                Chunk r[12];
                const unsigned* ps_[3];
#pragma unroll
                for (int k = 0; k < 3; k++) {
                    const int id = tid + 256 * k, j = id / 48;
                    ps_[k] = &p.g->qmail[cta0 + j * 4][(id - j * 48) * 4];
                }
                const unsigned* const ps[3] = {ps_[0], ps_[1], ps_[2]};
                mail_gather<12, 4>(ps, kDh, tag, r);
#pragma unroll
                for (int k = 0; k < 3; k++) {
                    float v[4];
#pragma unroll
                    for (int e = 0; e < 4; e++) v[e] = bfr((r[k * 4].v(e) + r[k * 4 + 1].v(e)) + (r[k * 4 + 2].v(e) + r[k * 4 + 3].v(e)));
                    reinterpret_cast<float4*>(&sm.q[0][0])[tid + 256 * k] = make_float4(v[0], v[1], v[2], v[3]);
                }
            }
            bar_sync(kBarCons, 256);

            {
                const int g = lane >> 3, c = lane & 7;
                const uint32_t lane_off = (uint32_t)((warp * 8 + g) * kRowB + c * 16);
                const float scale = 0.07216878364870322f;
#pragma unroll 1
                for (int j = 0; j < kGH; j++) {
                    const int t = kTK + j;
                    const uint32_t st = t % kStages;
                    float4 q[6];
#pragma unroll
                    for (int i = 0; i < 6; i++) q[i] = *reinterpret_cast<const float4*>(&sm.q[j][(i >> 1) * 64 + c * 8 + (i & 1) * 4]);
                    mbar_wait(full0 + 8 * st, (t / kStages) & 1);
                    const uint32_t a = ring0 + st * kTileB + lane_off;
                    uint4 v[6];
#pragma unroll
                    for (int i = 0; i < 3; i++) { v[i] = lds128(a + i * 128); v[3 + i] = lds128(a + 4 * kRowB + i * 128); }
                    const float s0 = dot8(q[0], q[1], v[0]) + dot8(q[2], q[3], v[1]) + dot8(q[4], q[5], v[2]);
                    const float s1 = dot8(q[0], q[1], v[3]) + dot8(q[2], q[3], v[4]) + dot8(q[4], q[5], v[5]);
                    __syncwarp();
                    if (lane == 0) mbar_arrive(empty0 + 8 * st);
                    float mine = (c & 4) ? s1 : s0;
                    const float other = (c & 4) ? s0 : s1;
                    mine += __shfl_xor_sync(0xffffffffu, other, 4);
                    mine += __shfl_xor_sync(0xffffffffu, mine, 2);
                    mine += __shfl_xor_sync(0xffffffffu, mine, 1);
                    if ((c & 3) == 0) sm.sc[j][warp * 8 + c + g] = bfr(bfr(mine) * scale);
                }
            }
            bar_sync(kBarCons, 256);
            {
                float4 sv = *reinterpret_cast<const float4*>(&sm.sc[0][tid * 4]);
                float m = fmaxf(fmaxf(sv.x, sv.y), fmaxf(sv.z, sv.w));
#pragma unroll
                for (int o = 8; o > 0; o >>= 1) m = fmaxf(m, __shfl_xor_sync(0xffffffffu, m, o));
                sv.x = __expf(sv.x - m); sv.y = __expf(sv.y - m); sv.z = __expf(sv.z - m); sv.w = __expf(sv.w - m);
                *reinterpret_cast<uint2*>(&sm.rowc[tid * 4]) = make_uint2(pack_bf16(sv.x, sv.y), pack_bf16(sv.z, sv.w));
                float l = (sv.x + sv.y) + (sv.z + sv.w);
#pragma unroll
                for (int o = 8; o > 0; o >>= 1) l += __shfl_xor_sync(0xffffffffu, l, o);
                if ((lane & 15) == 0) { sm.stat[(tid >> 4) * 2] = m; sm.stat[(tid >> 4) * 2 + 1] = l; }
            }
        }

        if (warp < 5) {
            const uint32_t* cw = reinterpret_cast<const uint32_t*>(sm.coef);
            int tqp = tq;
            asm volatile("" : "+r"(tqp));
            const bool q0 = tqp == 0, q1 = tqp == 1;
            float4* slot = acc_slot(p.g, (((cta & 1) * 5 + warp) * 8 + mg) * 3 + tq);
            __nv_bfloat16* o = p.out + ((cta & 1) * 5 + warp) * 64 + tq * 24 + mg;
            float d[4][4];
            uint32_t off[4], w0[8][4], w1[8][4];
            float f0, f1, f2;
#pragma unroll
            for (int i = 0; i < 4; i++) off[i] = lk * 128 + ((((2 * i + ((lane >> 3) & 1)) ^ lk) & 7) << 4);
            {
                const uint32_t b0 = cw[48 + tq], b1 = cw[52 + tq], b2 = cw[56 + tq], b3 = cw[60 + tq];
                const float gb = sm.gate[1];
                const uint32_t a = ring0 + (kTD % kStages) * kTileB + warp * kFC * 128;
                mbar_wait(full0 + 8 * (kTD % kStages), (kTD / kStages) & 1);
#pragma unroll
                for (int i = 0; i < 4; i++) {
                    ldsm4t(w0[i], a + off[i]);
                    ldsm4t(w0[4 + i], a + off[i] + (lane < 16 ? 16 : 8) * 128);
                }
#pragma unroll
                for (int i = 0; i < 4; i++) {
                    d[i][0] = d[i][1] = d[i][2] = d[i][3] = 0.f;
                    mma16816(d[i], w0[i], b0, b1);
                    mma16816(d[i], w0[4 + i], b2, b3);
                }
                f0 = gb * fsel(q0, d[0][0], fsel(q1, d[1][2], d[3][0]));
                f1 = gb * fsel(q0, d[0][2], fsel(q1, d[2][0], d[3][2]));
                f2 = gb * fsel(q0, d[1][0], d[2][2]);
            }
#pragma unroll
            for (int i = 0; i < 4; i++) off[i] += ring0 + warp * 32 * 128;
            asm volatile("" : "+r"(off[0]), "+r"(off[1]), "+r"(off[2]), "+r"(off[3]));
            mbar_wait(full0 + 8 * (kTO % kStages), (kTO / kStages) & 1);
#pragma unroll
            for (int i = 0; i < 8; i++) ldsm4t(w0[i], off[i & 3] + (kTO % kStages) * kTileB + (i >> 2) * 2048);
            uint32_t b[12];
            float ga = sm.gate[0];
#pragma unroll
            for (int i = 0; i < 4; i++) d[i][0] = d[i][1] = d[i][2] = d[i][3] = 0.f;
            const bool early = __all_sync(0xffffffffu, mbar_test(s2u(&sm.coef_ready), 0));
            if (early) {
#pragma unroll
                for (int j = 0; j < 12; j++) b[j] = cw[j * 4 + tq];
#pragma unroll
                for (int i = 0; i < 8; i++) mma16816(d[i & 3], w0[i], b[(i >> 2) * 2], b[(i >> 2) * 2 + 1]);
            }
            asm volatile("" : "+l"(slot), "+l"(o), "+f"(ga), "+f"(f0), "+f"(f1), "+f"(f2));
            mbar_wait(full0 + 8 * ((kTO + 1) % kStages), ((kTO + 1) / kStages) & 1);
#pragma unroll
            for (int i = 0; i < 8; i++) ldsm4t(w1[i], off[i & 3] + ((kTO + 1) % kStages) * kTileB + (i >> 2) * 2048);
            if (!early) {
                mbar_wait(s2u(&sm.coef_ready), 0);
#pragma unroll
                for (int j = 0; j < 12; j++) b[j] = cw[j * 4 + tq];
#pragma unroll
                for (int i = 0; i < 8; i++) mma16816(d[i & 3], w0[i], b[(i >> 2) * 2], b[(i >> 2) * 2 + 1]);
            }
#pragma unroll
            for (int i = 0; i < 8; i++) mma16816(d[i & 3], w1[i], b[4 + (i >> 2) * 2], b[5 + (i >> 2) * 2]);
            mbar_wait(full0 + 8 * ((kTO + 2) % kStages), ((kTO + 2) / kStages) & 1);
#pragma unroll
            for (int i = 0; i < 8; i++) ldsm4t(w0[i], off[i & 3] + ((kTO + 2) % kStages) * kTileB + (i >> 2) * 2048);
#pragma unroll
            for (int i = 0; i < 8; i++) mma16816(d[i & 3], w0[i], b[8 + (i >> 2) * 2], b[9 + (i >> 2) * 2]);
            const float v0 = fmaf(ga, fsel(q0, d[0][0], fsel(q1, d[1][2], d[3][0])), f0);
            const float v1 = fmaf(ga, fsel(q0, d[0][2], fsel(q1, d[2][0], d[3][2])), f1);
            const float v2 = fmaf(ga, fsel(q0, d[1][0], d[2][2]), f2);
            if (tqp < 3) {
                const float4 old = atom_add4(slot, v0, v1, v2, 1.0f);
                if (old.w == (float)(kCTAs / 2 - 1)) {
                    st_bf16(o, old.x + v0);
                    st_bf16(o + 8, old.y + v1);
                    if (tqp < 2) st_bf16(o + 16, old.z + v2);
                }
            }
        }
        if (warp < 6) return;
    }

    {
        const int tt = warp == kCW + 1 ? 64 + lane : tid - 192;
        const int half = (cta >> 1) & 1;
        bar_sync(kBarTeam, 96);
        mbar_wait(s2u(&sm.go[1]), 0);
        if (hl >= kGH - kLate) {
            if (tt < kOC / 2) {
                float4* slot = acc_slot(p.g, kSlots + ((cta >> 6) * kLate + hl - (kGH - kLate)) * kOSlots + half * (kOC / 2) + tt);
                float4 r;
                unsigned n = 0;
                do { r = atom_add4(slot, 0.f, 0.f, 0.f, 0.f); if (++n > kSpinLimit) __trap(); } while (r.w != (float)kGrp);
                const int d = (tt >> 4) * 32 + (tt & 1) * 16 + ((tt >> 1) & 7);
                sm.coef[d] = __float2bfloat16_rn(r.x);
                sm.coef[d + 8] = __float2bfloat16_rn(r.y);
            }
        } else {
            const int c = tt % 24, sg = tt / 24;
            const unsigned* const ps[1] = {&p.g->omail[hl][cta0 + sg][half * kOC + c * 4]};
            Chunk r[16];
            mail_gather<16>(ps, 4 * kDh, tag, r);
            float4 acc = make_float4(0.f, 0.f, 0.f, 0.f);
#pragma unroll
            for (int k = 0; k < 16; k++) {
                const float w = sm.wgt[sg + 4 * k];
                acc.x = fmaf(w, r[k].v(0), acc.x); acc.y = fmaf(w, r[k].v(1), acc.y);
                acc.z = fmaf(w, r[k].v(2), acc.z); acc.w = fmaf(w, r[k].v(3), acc.w);
            }
            *reinterpret_cast<float4*>(&sm.part[sg][c * 4]) = acc;
            bar_sync(kBarTeam, 96);
            if (tt < kOC / 2) {
                const float2 a = *reinterpret_cast<const float2*>(&sm.part[0][tt * 2]), b = *reinterpret_cast<const float2*>(&sm.part[1][tt * 2]);
                const float2 e = *reinterpret_cast<const float2*>(&sm.part[2][tt * 2]), f = *reinterpret_cast<const float2*>(&sm.part[3][tt * 2]);
                reinterpret_cast<uint32_t*>(sm.coef)[tt] = pack_bf16((a.x + b.x) + (e.x + f.x), (a.y + b.y) + (e.y + f.y));
            }
        }
        __syncwarp();
        if (tt < 64 && lane == 0) mbar_arrive(s2u(&sm.coef_ready));
    }
}

__device__ float g_fb[2 * kH * kDh + kF];
__device__ __forceinline__ float ldbf(const void* p, size_t i) { return __bfloat162float(reinterpret_cast<const __nv_bfloat16*>(p)[i]); }
__global__ void fb_proj(const void* x, const void* wq, const void* wg, const void* wu) {
    const int n = blockIdx.x * blockDim.x + threadIdx.x;
    if (n < kH * kDh) {
        float a = 0.f;
        for (int k = 0; k < kD; k++) a = fmaf(ldbf(x, k), ldbf(wq, (size_t)k * kH * kDh + n), a);
        g_fb[n] = bfr(a);
    } else if (n < kH * kDh + kF) {
        const int f = n - kH * kDh;
        float a = 0.f, b = 0.f;
        for (int k = 0; k < kD; k++) { a = fmaf(ldbf(x, k), ldbf(wg, (size_t)k * kF + f), a); b = fmaf(ldbf(x, k), ldbf(wu, (size_t)k * kF + f), b); }
        a = bfr(a);
        g_fb[2 * kH * kDh + f] = bfr((a > 0.f ? a : a * 0.f) * bfr(b));
    }
}
__global__ void fb_attn(const void* kc, const void* vc) {
    __shared__ float sc[kW], red[kDh];
    const int h = blockIdx.x, t = threadIdx.x;
    const size_t base = ((size_t)h * kSk + kSk - kW) * kDh;
    float m = -INFINITY, l = 0.f, o = 0.f;
    for (int k = t; k < kW; k += kDh) {
        float a = 0.f;
        for (int d = 0; d < kDh; d++) a = fmaf(g_fb[h * kDh + d], ldbf(kc, base + (size_t)k * kDh + d), a);
        sc[k] = bfr(bfr(a) * 0.07216878364870322f);
        m = fmaxf(m, sc[k]);
    }
    red[t] = m;
    __syncthreads();
    for (int i = 0; i < kDh; i++) m = fmaxf(m, red[i]);
    for (int k = 0; k < kW; k++) {
        const float e = __expf(sc[k] - m);
        l += e;
        o = fmaf(e, ldbf(vc, base + (size_t)k * kDh + t), o);
    }
    g_fb[kH * kDh + h * kDh + t] = bfr(o / l);
}
__global__ void fb_out(const void* x, const void* gw, const void* wo, const void* wd, __nv_bfloat16* out) {
    const int n = blockIdx.x * blockDim.x + threadIdx.x;
    float z = 0.f, a = 0.f, b = 0.f;
    for (int k = 0; k < kD; k++) z += bfr(ldbf(x, k) * ldbf(gw, k));
    const float g = bfr(1.0f / (1.0f + __expf(-bfr(z))));
    for (int k = 0; k < kH * kDh; k++) a = fmaf(g_fb[kH * kDh + k], ldbf(wo, (size_t)k * kD + n), a);
    for (int k = 0; k < kF; k++) b = fmaf(g_fb[2 * kH * kDh + k], ldbf(wd, (size_t)k * kD + n), b);
    out[n] = __float2bfloat16_rn(g * a + bfr(1.0f - g) * b);
}

typedef CUresult (*EncodeFn)(CUtensorMap*, CUtensorMapDataType, cuuint32_t, void*, const cuuint64_t*, const cuuint64_t*,
                             const cuuint32_t*, const cuuint32_t*, CUtensorMapInterleave, CUtensorMapSwizzle,
                             CUtensorMapL2promotion, CUtensorMapFloatOOBfill);

void make_map(EncodeFn fn, CUtensorMap* m, void* base, int rows, int cols, int box_rows) {
    const cuuint64_t dims[3] = {64, (cuuint64_t)(cols / 64), (cuuint64_t)rows};
    const cuuint64_t strides[2] = {128, (cuuint64_t)cols * 2};
    const cuuint32_t box[3] = {64, 3, (cuuint32_t)box_rows};
    const cuuint32_t estr[3] = {1, 1, 1};
    fn(m, CU_TENSOR_MAP_DATA_TYPE_BFLOAT16, 3, base, dims, strides, box, estr, CU_TENSOR_MAP_INTERLEAVE_NONE,
       CU_TENSOR_MAP_SWIZZLE_128B, CU_TENSOR_MAP_L2_PROMOTION_NONE, CU_TENSOR_MAP_FLOAT_OOB_FILL_NONE);
}
void make_map_out(EncodeFn fn, CUtensorMap* m, void* base, int rows, int box_rows) {
    const cuuint64_t dims[3] = {64, (cuuint64_t)rows, (cuuint64_t)(kD / 64)};
    const cuuint64_t strides[2] = {(cuuint64_t)kOutRowB, 128};
    const cuuint32_t box[3] = {64, (cuuint32_t)box_rows, 5};
    const cuuint32_t estr[3] = {1, 1, 1};
    fn(m, CU_TENSOR_MAP_DATA_TYPE_BFLOAT16, 3, base, dims, strides, box, estr, CU_TENSOR_MAP_INTERLEAVE_NONE,
       CU_TENSOR_MAP_SWIZZLE_128B, CU_TENSOR_MAP_L2_PROMOTION_NONE, CU_TENSOR_MAP_FLOAT_OOB_FILL_NONE);
}

}

extern "C" void kernel_launch(void* const* d_in, const int* in_sizes, int n_in, void* d_out, int out_size) {
    (void)in_sizes; (void)n_in; (void)out_size;
    static EncodeFn encode = nullptr;
    static void* scratch = nullptr;
    static int resident = -1;
    if (resident < 0) {
        cudaGetSymbolAddress(&scratch, g_scratch);
        void* fn = nullptr;
        cudaDriverEntryPointQueryResult qr;
        cudaGetDriverEntryPoint("cuTensorMapEncodeTiled", &fn, cudaEnableDefault, &qr);
        encode = (EncodeFn)fn;
        cudaFuncSetAttribute(fused_decode_kernel, cudaFuncAttributeMaxDynamicSharedMemorySize, (int)sizeof(Smem));
        int dev = 0, sms = 0, per_sm = 0;
        cudaGetDevice(&dev);
        cudaDeviceGetAttribute(&sms, cudaDevAttrMultiProcessorCount, dev);
        cudaOccupancyMaxActiveBlocksPerMultiprocessor(&per_sm, fused_decode_kernel, kThreads, sizeof(Smem));
        resident = sms * per_sm;
    }
    if (resident < kCTAs || !encode) {
        fb_proj<<<(kH * kDh + kF) / 128, 128, 0, cudaStreamPerThread>>>(d_in[0], d_in[3], d_in[6], d_in[7]);
        fb_attn<<<kH, kDh, 0, cudaStreamPerThread>>>(d_in[1], d_in[2]);
        fb_out<<<kD / 32, 32, 0, cudaStreamPerThread>>>(d_in[0], d_in[9], d_in[4], d_in[8], (__nv_bfloat16*)d_out);
        return;
    }
    Params p;
    p.x = (const __nv_bfloat16*)d_in[0];
    p.k = (const unsigned char*)d_in[1];
    p.gate_w = (const __nv_bfloat16*)d_in[9];
    p.out = (__nv_bfloat16*)d_out;
    p.g = (Scratch*)scratch;
    make_map(encode, &p.tq, d_in[3], kD, kH * kDh, 32);
    make_map(encode, &p.tg, d_in[6], kD, kF, 16);
    make_map(encode, &p.tu, d_in[7], kD, kF, 16);
    make_map(encode, &p.tv, d_in[2], kH * kSk, kDh, kTileKeys);
    make_map_out(encode, &p.td, d_in[8], kF, kFC);
    make_map_out(encode, &p.to, d_in[4], kH * kDh, 32);
    cudaLaunchConfig_t cfg = {};
    cfg.gridDim = dim3(kCTAs);
    cfg.blockDim = dim3(kThreads);
    cfg.dynamicSmemBytes = sizeof(Smem);
    cfg.stream = cudaStreamPerThread;
    cudaLaunchAttribute attr;
    attr.id = cudaLaunchAttributeCooperative;
    attr.val.cooperative = 1;
    cfg.attrs = &attr;
    cfg.numAttrs = 1;
    cudaLaunchKernelEx(&cfg, fused_decode_kernel, (const unsigned char*)d_in[3], p);
}
```

```cpp
#include <cuda_runtime.h>
#include <cuda_bf16.h>
#include <cuda.h>
#include <math.h>
#include <stdint.h>

namespace {

constexpr int kD = 640;
constexpr int kH = 32;
constexpr int kDh = 192;
constexpr int kSk = 32768;
constexpr int kW = 4096;
constexpr int kF = 1536;
constexpr int kCTAs = 128;
constexpr int kGrp = 64;
constexpr int kGH = kH * kGrp / kCTAs;
constexpr int kCW = 8;
constexpr int kThreads = kCW * 32 + 64;
constexpr int kTileKeys = kW / kGrp;
constexpr int kRowB = kDh * 2;
constexpr int kTileB = kTileKeys * kRowB;
constexpr int kStages = 8;
constexpr int kOutRowB = kD * 2;
constexpr int kFC = 2 * kF / kCTAs;
constexpr int kOC = 2 * kH * kDh / kCTAs;
constexpr int kXR = kD / 4;
constexpr int kFR = kD / 8;
constexpr int kTQ = 0;
constexpr int kTK = 3;
constexpr int kTF = kTK + kGH;
constexpr int kTV = kTF + 2;
constexpr int kTD = kTV + kGH;
constexpr int kTO = kTD + 1;
constexpr int kNumTiles = kTO + 3;
constexpr int kSlots = 240;
constexpr int kLate = 4;
constexpr int kOSlots = kDh / 2;
constexpr int kLateSlots = 2 * kLate * kOSlots;
constexpr unsigned kSpinLimit = 1u << 24;
static_assert(kTD - kLate + kStages > kNumTiles - 1, "the producer must be able to finish before the late V tiles are consumed");

constexpr uint32_t kWindow = 62000;
static_assert(kWindow >= 2 * kTileB, "a leading CTA still waits for an earlier tile");
constexpr int kBalStart = 8;
constexpr int kLead0 = 8, kLead1 = 56, kLead2 = 120;
constexpr int kMile = 576, kMileLate = 384;
constexpr unsigned kMileQ = 400;

constexpr int kCbQ = kGH * kTileKeys, kCbF = kCbQ + kXR, kCbLen = kCbF + kFR;

struct Smem {
    alignas(1024) unsigned char ring[kStages][kTileB];
    alignas(16) float q[kGH][kDh];
    alignas(16) float sc[kGH][kTileKeys];
    alignas(16) __nv_bfloat16 rowc[kCbLen];
    alignas(16) __nv_bfloat16 coef[128];
    alignas(16) float part[4][kOC];
    float wgt[kGrp];
    float lscale[kLate];
    float stat[2 * kGH];
    float gate[2];
    unsigned tag;
    alignas(8) unsigned long long full[kStages];
    alignas(8) unsigned long long empty[kStages];
    alignas(8) unsigned long long coef_ready;
    alignas(8) unsigned long long go[2];
};

struct Scratch {
    alignas(256) unsigned epoch;
    alignas(256) unsigned accflag;
    alignas(256) unsigned prog;
    alignas(256) float4 acc[(kSlots / 6 + kLateSlots / 4) * 16];
    alignas(256) unsigned stat[kCTAs][2 * kGH];
    alignas(256) unsigned qmail[kCTAs][kDh];
    alignas(256) unsigned fmail[kCTAs][kDh];
    alignas(256) unsigned omail[kGH - kLate][kCTAs][kDh];
};
__device__ Scratch g_scratch;

__device__ __forceinline__ uint32_t s2u(const void* p) { return (uint32_t)__cvta_generic_to_shared(p); }

__device__ __forceinline__ void mbar_init(uint32_t bar, uint32_t cnt) {
    asm volatile("mbarrier.init.shared::cta.b64 [%0], %1;" ::"r"(bar), "r"(cnt) : "memory");
}
__device__ __forceinline__ void mbar_expect_tx(uint32_t bar, uint32_t bytes) {
    asm volatile("mbarrier.arrive.expect_tx.shared::cta.b64 _, [%0], %1;" ::"r"(bar), "r"(bytes) : "memory");
}
__device__ __forceinline__ void mbar_arrive(uint32_t bar, uint32_t cnt = 1) {
    asm volatile("mbarrier.arrive.shared::cta.b64 _, [%0], %1;" ::"r"(bar), "r"(cnt) : "memory");
}
__device__ __forceinline__ void mbar_wait(uint32_t bar, uint32_t parity) {
    asm volatile("{\n.reg .pred p;\n.reg .u32 n;\nmov.u32 n, 0;\n"
                 "WL:\nmbarrier.try_wait.parity.shared::cta.b64 p, [%0], %1;\n@p bra WD;\n"
                 "add.u32 n, n, 1;\nsetp.lt.u32 p, n, %2;\n@p bra WL;\ntrap;\nWD:\n}"
                 ::"r"(bar), "r"(parity), "n"(kSpinLimit) : "memory");
}
__device__ __forceinline__ bool mbar_test(uint32_t bar, uint32_t parity) {
    uint32_t ok;
    asm volatile("{\n.reg .pred p;\nmbarrier.test_wait.parity.shared::cta.b64 p, [%1], %2;\nselp.u32 %0, 1, 0, p;\n}"
                 : "=r"(ok) : "r"(bar), "r"(parity) : "memory");
    return ok != 0;
}
__device__ __forceinline__ void bulk_g2s(uint32_t dst, const void* src, uint32_t bytes, uint32_t bar, uint64_t pol) {
    asm volatile("cp.async.bulk.shared::cluster.global.mbarrier::complete_tx::bytes.L2::cache_hint [%0], [%1], %2, [%3], %4;"
                 ::"r"(dst), "l"(src), "r"(bytes), "r"(bar), "l"(pol) : "memory");
}
__device__ __forceinline__ void tma_3d(uint32_t dst, const CUtensorMap* map, int c1, int c2, uint32_t bar, uint64_t pol) {
    asm volatile("cp.async.bulk.tensor.3d.shared::cluster.global.mbarrier::complete_tx::bytes.L2::cache_hint [%0], [%1, {%4, %3, %6}], [%2], %5;"
                 ::"r"(dst), "l"(map), "r"(bar), "r"(c1), "r"(0), "l"(pol), "r"(c2) : "memory");
}
__device__ __forceinline__ void ldsm4t(uint32_t (&r)[4], uint32_t a) {
    asm volatile("ldmatrix.sync.aligned.m8n8.x4.trans.shared.b16 {%0,%1,%2,%3}, [%4];"
                 : "=r"(r[0]), "=r"(r[1]), "=r"(r[2]), "=r"(r[3]) : "r"(a));
}
__device__ __forceinline__ void mma16816(float (&d)[4], const uint32_t (&a)[4], uint32_t b0, uint32_t b1) {
    asm volatile("mma.sync.aligned.m16n8k16.row.col.f32.bf16.bf16.f32 {%0,%1,%2,%3}, {%4,%5,%6,%7}, {%8,%9}, {%0,%1,%2,%3};"
                 : "+f"(d[0]), "+f"(d[1]), "+f"(d[2]), "+f"(d[3]) : "r"(a[0]), "r"(a[1]), "r"(a[2]), "r"(a[3]), "r"(b0), "r"(b1));
}
__device__ __forceinline__ uint4 ldg128(const void* p) {
    uint4 v;
    asm volatile("ld.global.nc.v4.u32 {%0,%1,%2,%3}, [%4];" : "=r"(v.x), "=r"(v.y), "=r"(v.z), "=r"(v.w) : "l"(p));
    return v;
}
__device__ __forceinline__ uint4 lds128(uint32_t a) {
    uint4 v;
    asm volatile("ld.shared.v4.u32 {%0,%1,%2,%3}, [%4];" : "=r"(v.x), "=r"(v.y), "=r"(v.z), "=r"(v.w) : "r"(a));
    return v;
}

__device__ __forceinline__ void word_st(unsigned* p, float v, unsigned tag) {
    asm volatile("st.relaxed.gpu.global.u32 [%0], %1;" ::"l"(p), "r"((__float_as_uint(v) & ~3u) | tag) : "memory");
}
__device__ __forceinline__ float word_val(unsigned w) { return __uint_as_float(w & ~3u); }
struct Chunk {
    unsigned w[4];
    __device__ __forceinline__ float v(int i) const { return word_val(w[i]); }
};
__device__ __forceinline__ unsigned mail_poll(const unsigned* p) {
    unsigned r;
    asm volatile("atom.relaxed.gpu.global.or.b32 %0, [%1], 0;" : "=r"(r) : "l"(p) : "memory");
    return r;
}
template <int N, int NP = N>
__device__ __forceinline__ void mail_gather(const unsigned* const (&p)[N / NP], int stride, unsigned tag, Chunk (&r)[N]) {
#pragma unroll
    for (int i = 0; i < N; i++) {
        asm volatile("ld.relaxed.gpu.global.v4.u32 {%0,%1,%2,%3}, [%4];"
                     : "=r"(r[i].w[0]), "=r"(r[i].w[1]), "=r"(r[i].w[2]), "=r"(r[i].w[3])
                     : "l"(p[i / NP] + (i % NP) * stride) : "memory");
    }
    unsigned n = 0;
#pragma unroll 1
    while (true) {
        unsigned bad = 0;
#pragma unroll
        for (int i = 0; i < N; i++)
            bad |= (((r[i].w[0] ^ tag) | (r[i].w[1] ^ tag) | (r[i].w[2] ^ tag) | (r[i].w[3] ^ tag)) & 3u) ? 1u << i : 0u;
        bad = __reduce_or_sync(0xffffffffu, bad);
        if (bad == 0) break;
        __nanosleep(200);
#pragma unroll
        for (int i = 0; i < N; i++) {
            if (bad >> i & 1) {
#pragma unroll
                for (int e = 0; e < 4; e++) r[i].w[e] = mail_poll(p[i / NP] + (i % NP) * stride + e);
            }
        }
        if (++n > kSpinLimit) __trap();
    }
}
__device__ __forceinline__ void word_wait(const unsigned* p, unsigned tag) {
    unsigned n = 0;
    while ((mail_poll(p) ^ tag) & 3u) { __nanosleep(100); if (++n > kSpinLimit) __trap(); }
}

__device__ __forceinline__ float4 atom_add4(float4* p, float a, float b, float c, float d) {
    float4 r;
    asm volatile("atom.relaxed.gpu.global.add.v4.f32 {%0,%1,%2,%3}, [%4], {%5,%6,%7,%8};"
                 : "=f"(r.x), "=f"(r.y), "=f"(r.z), "=f"(r.w) : "l"(p), "f"(a), "f"(b), "f"(c), "f"(d) : "memory");
    return r;
}
__device__ __forceinline__ float4* out_slot(Scratch* g, int i) { return &g->acc[(i / 6) * 16 + i % 6]; }
__device__ __forceinline__ float4* late_slot(Scratch* g, int i) { return &g->acc[kSlots / 6 * 16 + (i >> 2) * 16 + (i & 3)]; }

enum { kBarCons = 1, kBarStart = 2, kBarStats = 3, kBarScalars = 4, kBarTeam = 5, kBarInit = 6 };
__device__ __forceinline__ void bar_sync(int id, int n) { asm volatile("barrier.sync %0, %1;" ::"r"(id), "r"(n) : "memory"); }
__device__ __forceinline__ void bar_arrive(int id, int n) { asm volatile("barrier.arrive %0, %1;" ::"r"(id), "r"(n) : "memory"); }

__device__ __forceinline__ void st_bf16(__nv_bfloat16* p, float v) {
    asm volatile("st.global.u16 [%0], %1;" ::"l"(p), "h"(__bfloat16_as_ushort(__float2bfloat16_rn(v))) : "memory");
}
__device__ __forceinline__ float fsel(bool c, float a, float b) {
    float r;
    asm("{\n.reg .pred p;\nsetp.ne.u32 p, %3, 0;\nselp.f32 %0, %1, %2, p;\n}" : "=f"(r) : "f"(a), "f"(b), "r"((unsigned)c));
    return r;
}
__device__ __forceinline__ float bf_lo(uint32_t w) { return __uint_as_float(w << 16); }
__device__ __forceinline__ float bf_hi(uint32_t w) { return __uint_as_float(w & 0xffff0000u); }
__device__ __forceinline__ float bfr(float v) { return __bfloat162float(__float2bfloat16_rn(v)); }
__device__ __forceinline__ uint32_t pack_bf16(float lo, float hi) {
    const __nv_bfloat162 v = __floats2bfloat162_rn(lo, hi);
    return *reinterpret_cast<const uint32_t*>(&v);
}
__device__ __forceinline__ float dot8(const float4& qa, const float4& qb, const uint4& v) {
    float a = qa.x * bf_lo(v.x), b = qa.y * bf_hi(v.x);
    a = fmaf(qa.z, bf_lo(v.y), a); b = fmaf(qa.w, bf_hi(v.y), b);
    a = fmaf(qb.x, bf_lo(v.z), a); b = fmaf(qb.y, bf_hi(v.z), b);
    a = fmaf(qb.z, bf_lo(v.w), a); b = fmaf(qb.w, bf_hi(v.w), b);
    return a + b;
}
__device__ __forceinline__ bool elect_one() {
    uint32_t ok;
    asm volatile("{\n.reg .pred p;\nelect.sync _|p, 0xffffffff;\nselp.u32 %0, 1, 0, p;\n}" : "=r"(ok));
    return ok != 0;
}

__host__ __device__ constexpr uint32_t tile_bytes(int t) {
    return (t == kTQ + 2 || t == kTF + 1) ? 32 * kRowB
         : t == kTF ? 48 * kRowB
         : t == kTD ? kFC * kOutRowB / 2
         : t >= kTO ? 32 * kOutRowB / 2 : kTileB;
}
constexpr uint64_t pack_back(int first) {
    uint64_t r = 0;
    for (int t = first; t < first + 21 && t < kNumTiles; t++) {
        uint32_t sum = 0;
        int j = t;
        for (; j >= 0; j--) { sum += tile_bytes(j); if (sum > kWindow) break; }
        r |= (uint64_t)(t - j > 5 ? 5 : t - j) << (3 * (t - first));
    }
    return r;
}
constexpr uint64_t kBackA = pack_back(0), kBackB = pack_back(21);
__device__ __forceinline__ int look_back(int t) {
    return (int)(((t < 21 ? kBackA : kBackB) >> (3 * (t < 21 ? t : t - 21))) & 7);
}

struct Params {
    const __nv_bfloat16* x;
    const unsigned char* k;
    const __nv_bfloat16* gate_w;
    __nv_bfloat16* out;
    Scratch* g;
    CUtensorMap tq;
    CUtensorMap tg;
    CUtensorMap tu;
    CUtensorMap tv;
    CUtensorMap td;
    CUtensorMap to;
};

__global__ void __launch_bounds__(kThreads, 1)
fused_decode_kernel(const unsigned char* __restrict__ wq, const __grid_constant__ Params p) {
    if (threadIdx.x == 0)
        asm volatile("cp.async.bulk.prefetch.L2.global [%0], %1;"
                     ::"l"(wq + (size_t)((blockIdx.x >> 5) * kXR + (blockIdx.x & 31)) * (kH * kRowB)), "n"(kH * kRowB) : "memory");
    extern __shared__ __align__(1024) unsigned char smem_raw[];
    Smem& sm = *reinterpret_cast<Smem*>(smem_raw);
    const int tid = threadIdx.x;
    const int lane = tid & 31;
    const int warp = tid >> 5;
    const int cta = blockIdx.x;
    const int cta0 = cta & ~(kGrp - 1);
    const int hl = (cta >> 2) & (kGH - 1);
    const uint32_t ring0 = s2u(&sm.ring[0][0]);
    const uint32_t full0 = s2u(&sm.full[0]);
    const uint32_t empty0 = s2u(&sm.empty[0]);

    uint64_t pol;
    asm volatile("createpolicy.fractional.L2::evict_first.b64 %0, 1.0;" : "=l"(pol));
    if (warp == kCW && elect_one()) {
#pragma unroll
        for (int i = 0; i < kTK; i++) mbar_init(full0 + 8 * i, 1);
        asm volatile("fence.mbarrier_init.release.cluster;" ::: "memory");
#pragma unroll
        for (int i = 0; i < kTK; i++) {
            const int row = (cta & 3) * kXR + i * 64;
            mbar_expect_tx(full0 + 8 * i, tile_bytes(i));
            tma_3d(ring0 + i * kTileB, &p.tq, (cta >> 2) * 3, row, full0 + 8 * i, pol);
            if (i < 2) tma_3d(ring0 + i * kTileB + 32 * kRowB, &p.tq, (cta >> 2) * 3, row + 32, full0 + 8 * i, pol);
        }
    }
    __syncwarp();

    if (warp == kCW) {
        const bool leader = elect_one();
        bar_sync(kBarInit, 64);
        bar_arrive(kBarStart, kThreads);
        const int key0 = (cta >> 6) * kGH * kSk + (kSk - kW) + (cta & (kGrp - 1)) * kTileKeys;
        const unsigned char* src = p.k + (size_t)key0 * kRowB;
        constexpr unsigned kProgMax = (kNumTiles - kTK) * kCTAs - 1;
        unsigned prog = 0;
        constexpr int kNever = 1 << 30;
        int mile0 = (kTV - 1 - kTK) * kCTAs + kMile, mile1 = (kTV + hl - kTK) * kCTAs + (hl < kGH - kLate ? kMile : kMileLate);
#pragma unroll 1
        for (int t = kTK; t < kNumTiles; t++) {
            const uint32_t st = t % kStages;
            const uint32_t dst = ring0 + st * kTileB, bar = full0 + 8 * st;
            if (t >= kStages) mbar_wait(empty0 + 8 * st, ((t / kStages) - 1) & 1);
            if (leader) mbar_expect_tx(bar, tile_bytes(t));
            int need = t - look_back(t);
            if (t >= kBalStart) {
                const int gp = (int)__shfl_sync(0xffffffffu, prog, 0);
                const int lead = (t - kTK) * kCTAs - gp;
                need += (lead > kLead2) - (lead <= kLead1) - (lead <= kLead0);
                const int seen = t == kNumTiles - 1 ? kNever - 1 : gp;
                if (seen >= mile0) { mile0 = kNever; if (leader) mbar_arrive(s2u(&sm.go[0])); }
                if (seen >= mile1) { mile1 = kNever; if (leader) mbar_arrive(s2u(&sm.go[1])); }
            }
            if (need >= 0) mbar_wait(full0 + 8 * (need % kStages), (need / kStages) & 1);
            if (leader) {
                if (t < kTF) {
                    bulk_g2s(dst, src, kTileB, bar, pol);
                } else if (t < kTV) {
                    const CUtensorMap* m = cta < 64 ? &p.tg : &p.tu;
                    const int row = (cta & 7) * kFR + (t - kTF) * 48, blk = ((cta >> 3) & 7) * 3;
                    tma_3d(dst, m, blk, row, bar, pol);
                    tma_3d(dst + 16 * kRowB, m, blk, row + 16, bar, pol);
                    if (t == kTF) tma_3d(dst + 32 * kRowB, m, blk, row + 32, bar, pol);
                } else if (t < kTD) {
                    tma_3d(dst, &p.tv, 0, key0 + (t - kTV) * kSk, bar, pol);
                } else {
                    tma_3d(dst, t == kTD ? &p.td : &p.to, t == kTD ? (cta >> 1) * kFC : (cta >> 1) * kOC + (t - kTO) * 32,
                           (cta & 1) * 5, bar, pol);
                }
            }
            if (leader && t == 12) {
                asm volatile("prefetch.tensormap [%0];" ::"l"(cta < 64 ? &p.tg : &p.tu) : "memory");
                asm volatile("prefetch.tensormap [%0];" ::"l"(&p.tv) : "memory");
                asm volatile("prefetch.tensormap [%0];" ::"l"(&p.td) : "memory");
                asm volatile("prefetch.tensormap [%0];" ::"l"(&p.to) : "memory");
            }
            src += (size_t)kSk * kRowB;
            if (lane == 0) {
                if (t + 1 >= kBalStart)
                    asm volatile("atom.relaxed.gpu.global.inc.u32 %0, [%1], %2;" : "=r"(prog) : "l"(&p.g->prog), "n"(kProgMax) : "memory");
                else
                    asm volatile("red.relaxed.gpu.global.inc.u32 [%0], %1;" ::"l"(&p.g->prog), "n"(kProgMax) : "memory");
            }
        }
        if (lane == 0 && prog == kProgMax) p.g->epoch = sm.tag;
        return;
    }

    unsigned tag;
    if (warp == kCW + 1) {
        if (elect_one()) {
#pragma unroll
            for (int i = 0; i < kStages; i++) { if (i >= kTK) mbar_init(full0 + 8 * i, 1); mbar_init(empty0 + 8 * i, kCW); }
            mbar_init(s2u(&sm.coef_ready), 2);
            mbar_init(s2u(&sm.go[0]), 1);
            mbar_init(s2u(&sm.go[1]), 1);
            asm volatile("fence.mbarrier_init.release.cluster;" ::: "memory");
        }
        __syncwarp();
        bar_arrive(kBarInit, 64);
        unsigned e = 0;
        if (lane == 31) asm volatile("ld.relaxed.gpu.global.u32 %0, [%1];" : "=r"(e) : "l"(&p.g->epoch) : "memory");
        if (lane < 30) {
            const uint4 v = ldg128(p.x + (lane < 20 ? (cta & 3) * kXR + lane * 8 : (cta & 7) * kFR + (lane - 20) * 8));
            *reinterpret_cast<uint4*>(&sm.rowc[kCbQ + lane * 8]) = v;
        }
        tag = __shfl_sync(0xffffffffu, e, 31) % 3u + 1u;
        if (lane == 0) sm.tag = tag;
        bar_arrive(kBarStart, kThreads);
        __nanosleep(3000);
        if (cta == 0) {
            for (int i = lane; i < kSlots; i += 32) *out_slot(p.g, i) = make_float4(0.f, 0.f, 0.f, 0.f);
            for (int i = lane; i < kLateSlots; i += 32) *late_slot(p.g, i) = make_float4(0.f, 0.f, 0.f, 0.f);
            __threadfence();
            __syncwarp();
            if (lane == 0) { __threadfence(); word_st(&p.g->accflag, 0.f, tag); }
        }
        {
            float z = 0.f;
#pragma unroll 1
            for (int j = lane; j < kD / 8; j += 32) {
                const uint4 gx = ldg128(p.x + j * 8), gw = ldg128(p.gate_w + j * 8);
                z += bfr(bf_lo(gx.x) * bf_lo(gw.x)) + bfr(bf_hi(gx.x) * bf_hi(gw.x));
                z += bfr(bf_lo(gx.y) * bf_lo(gw.y)) + bfr(bf_hi(gx.y) * bf_hi(gw.y));
                z += bfr(bf_lo(gx.z) * bf_lo(gw.z)) + bfr(bf_hi(gx.z) * bf_hi(gw.z));
                z += bfr(bf_lo(gx.w) * bf_lo(gw.w)) + bfr(bf_hi(gx.w) * bf_hi(gw.w));
            }
#pragma unroll
            for (int o = 16; o > 0; o >>= 1) z += __shfl_xor_sync(0xffffffffu, z, o);
            const float gate = bfr(1.0f / (1.0f + __expf(-bfr(z))));
            if (lane == 0) { sm.gate[0] = gate; sm.gate[1] = bfr(1.0f - gate); }
            if (lane < 8) sm.coef[kOC + kFC + lane] = __float2bfloat16_rn(0.f);
        }
        __nanosleep(2000);
        if (lane == 0) {
            word_wait(&p.g->accflag, tag);
            __threadfence();
        }
        __syncwarp();
        bar_sync(kBarStats, 288);
        word_st(&p.g->stat[cta][lane], sm.stat[lane], tag);
        mbar_wait(s2u(&sm.go[0]), 0);
        {
            const int mtx = lane >> 4, rb = (lane >> 1) & 7, half = lane & 1;
            const unsigned* sa = p.g->stat[cta0 + lane];
            const unsigned* sb = p.g->stat[cta0 + 32 + lane];
            const unsigned* fm = &p.g->fmail[(mtx * 8 + (cta >> 4)) * 8 + rb][((cta >> 1) & 7) * kFC + half * 12];
            const unsigned* const ps[9] = {sa + (hl >> 1) * 4, sb + (hl >> 1) * 4, sa + 24, sb + 24, sa + 28, sb + 28, fm, fm + 4, fm + 8};
            Chunk r[9];
            mail_gather<9, 1>(ps, 0, tag, r);
#pragma unroll 1
            for (int i = -1; i < kLate; i++) {
                const int hd = i < 0 ? hl : kGH - kLate + i;
                const Chunk a = i < 0 ? r[0] : hd < 14 ? r[2] : r[4], b = i < 0 ? r[1] : hd < 14 ? r[3] : r[5];
                const float m0 = hd & 1 ? a.v(2) : a.v(0), l0 = hd & 1 ? a.v(3) : a.v(1);
                const float m1 = hd & 1 ? b.v(2) : b.v(0), l1 = hd & 1 ? b.v(3) : b.v(1);
                float M = fmaxf(m0, m1);
#pragma unroll
                for (int o = 16; o > 0; o >>= 1) M = fmaxf(M, __shfl_xor_sync(0xffffffffu, M, o));
                const float w0 = __expf(m0 - M), w1 = __expf(m1 - M);
                float L = w0 * l0 + w1 * l1;
#pragma unroll
                for (int o = 16; o > 0; o >>= 1) L += __shfl_xor_sync(0xffffffffu, L, o);
                if (i < 0) { sm.wgt[lane] = w0 / L; sm.wgt[lane + 32] = w1 / L; }
                else if (lane == (cta & 31)) sm.lscale[i] = ((cta & 32) ? w1 : w0) / L;
            }
#pragma unroll
            for (int j = 0; j < 12; j++) {
                float v = r[6 + (j >> 2)].v(j & 3);
                v += __shfl_xor_sync(0xffffffffu, v, 2);
                v += __shfl_xor_sync(0xffffffffu, v, 4);
                v += __shfl_xor_sync(0xffffffffu, v, 8);
                const float gt = bfr(v);
                const float up = __shfl_xor_sync(0xffffffffu, gt, 16);
                if (lane < 2) sm.coef[kOC + half * 12 + j] = __float2bfloat16_rn((gt > 0.f ? gt : gt * 0.f) * up);
            }
        }
        bar_arrive(kBarScalars, 224);
    } else {
        bar_sync(kBarStart, kThreads);
        tag = sm.tag;

        const int mg = lane >> 2, tq = lane & 3;
        const int lk = (lane & 7) + ((lane >> 4) << 3);
        uint32_t voff[2];
#pragma unroll
        for (int i = 0; i < 2; i++) {
            const int line = lk * 3 + (warp >> 1);
            voff[i] = line * 128 + (((((warp & 1) * 4 + 2 * i + ((lane >> 3) & 1)) ^ line) & 7) << 4);
        }
#pragma unroll 1
        for (int pass = 0; pass < 3; pass++) {
            if (warp < 6) {
                const int t0 = pass == 0 ? kTQ : (pass == 1 ? kTF : kTV);
                const int t1 = pass == 0 ? kTK : (pass == 1 ? kTV : kTD);
                const uint32_t* cf = reinterpret_cast<const uint32_t*>(&sm.rowc[pass == 0 ? kCbQ : (pass == 1 ? kCbF : 0)]) + tq;
                float d[4][4];
#pragma unroll
                for (int i = 0; i < 4; i++) d[i][0] = d[i][1] = d[i][2] = d[i][3] = 0.f;
#pragma unroll 1
                for (int t = t0; t < t1; t++) {
                    const uint32_t st = t % kStages;
                    const int nk = tile_bytes(t) / (16 * kRowB);
                    if (t == kTD - kLate) bar_sync(kBarScalars, 224);
                    uint32_t b[8];
#pragma unroll
                    for (int j = 0; j < 8; j++) b[j] = cf[j * 4];
                    cf += nk * 8;
                    const bool late = t >= kTD - kLate;
                    const float ls = sm.lscale[late ? t - (kTD - kLate) : 0];
                    void* dst = late ? (void*)late_slot(p.g, ((cta >> 6) * kLate + t - (kTD - kLate)) * kOSlots + warp * 16 + mg * 2 + (tq >> 1))
                                     : (void*)((t < kTK ? p.g->qmail[cta] : t < kTV ? p.g->fmail[cta] : p.g->omail[t - kTV][cta]) + warp * 32 + tq * 8 + mg);
                    mbar_wait(full0 + 8 * st, (t / kStages) & 1);
                    const uint32_t a = ring0 + st * kTileB;
                    uint32_t w[8][4];
#pragma unroll
                    for (int j = 0; j < 4; j++) ldsm4t(w[j], a + voff[j & 1] + (j >> 1) * (16 * kRowB));
                    if (nk > 2) {
                        ldsm4t(w[4], a + voff[0] + 2 * (16 * kRowB));
                        ldsm4t(w[5], a + voff[1] + 2 * (16 * kRowB));
                    }
                    if (nk > 3) {
                        ldsm4t(w[6], a + voff[0] + 3 * (16 * kRowB));
                        ldsm4t(w[7], a + voff[1] + 3 * (16 * kRowB));
                    }
#pragma unroll
                    for (int j = 0; j < 4; j++) mma16816(d[j], w[j], b[(j >> 1) * 2], b[(j >> 1) * 2 + 1]);
                    if (nk > 2) { mma16816(d[0], w[4], b[4], b[5]); mma16816(d[1], w[5], b[4], b[5]); }
                    if (nk > 3) { mma16816(d[2], w[6], b[6], b[7]); mma16816(d[3], w[7], b[6], b[7]); }
                    if (pass == 2 || t == t1 - 1) {
                        const float c0 = fsel(tq & 2, d[1][0] + d[3][0], d[0][0] + d[2][0]);
                        const float c8 = fsel(tq & 2, d[1][2] + d[3][2], d[0][2] + d[2][2]);
                        if (!late) word_st((unsigned*)dst, fsel(tq & 1, c8, c0), tag);
                        else if (!(tq & 1))
                            asm volatile("red.relaxed.gpu.global.add.v4.f32 [%0], {%1,%2,%3,%4};"
                                         ::"l"(dst), "f"(c0 * ls), "f"(c8 * ls), "f"(0.f), "f"(1.f) : "memory");
#pragma unroll
                        for (int i = 0; i < 4; i++) d[i][0] = d[i][1] = d[i][2] = d[i][3] = 0.f;
                    }
                    __syncwarp();
                    if (lane == 0) mbar_arrive(empty0 + 8 * st, warp < 2 ? 2 : 1);
                }
            }
            if (pass == 1) bar_sync(kBarStats, 288);
            if (pass != 0) continue;

            if (tid == kDh) {
                mbar_wait(full0 + 8 * kTK, 0);
                for (int n = 0; n < 64 && mail_poll(&p.g->prog) < kMileQ; n++) __nanosleep(150);
            }
            bar_sync(kBarCons, 256);
            {
                Chunk r[12];
                const unsigned* ps_[3];
#pragma unroll
                for (int k = 0; k < 3; k++) {
                    const int id = tid + 256 * k, j = id / 48;
                    ps_[k] = &p.g->qmail[cta0 + j * 4][(id - j * 48) * 4];
                }
                const unsigned* const ps[3] = {ps_[0], ps_[1], ps_[2]};
                mail_gather<12, 4>(ps, kDh, tag, r);
#pragma unroll
                for (int k = 0; k < 3; k++) {
                    float v[4];
#pragma unroll
                    for (int e = 0; e < 4; e++) v[e] = bfr((r[k * 4].v(e) + r[k * 4 + 1].v(e)) + (r[k * 4 + 2].v(e) + r[k * 4 + 3].v(e)));
                    reinterpret_cast<float4*>(&sm.q[0][0])[tid + 256 * k] = make_float4(v[0], v[1], v[2], v[3]);
                }
            }
            bar_sync(kBarCons, 256);

            {
                const int g = lane >> 3, c = lane & 7;
                const uint32_t lane_off = (uint32_t)((warp * 8 + g) * kRowB + c * 16);
                const float scale = 0.07216878364870322f;
#pragma unroll 1
                for (int j = 0; j < kGH; j++) {
                    const int t = kTK + j;
                    const uint32_t st = t % kStages;
                    float4 q[6];
#pragma unroll
                    for (int i = 0; i < 6; i++) q[i] = *reinterpret_cast<const float4*>(&sm.q[j][(i >> 1) * 64 + c * 8 + (i & 1) * 4]);
                    mbar_wait(full0 + 8 * st, (t / kStages) & 1);
                    const uint32_t a = ring0 + st * kTileB + lane_off;
                    uint4 v[6];
#pragma unroll
                    for (int i = 0; i < 3; i++) { v[i] = lds128(a + i * 128); v[3 + i] = lds128(a + 4 * kRowB + i * 128); }
                    const float s0 = dot8(q[0], q[1], v[0]) + dot8(q[2], q[3], v[1]) + dot8(q[4], q[5], v[2]);
                    const float s1 = dot8(q[0], q[1], v[3]) + dot8(q[2], q[3], v[4]) + dot8(q[4], q[5], v[5]);
                    __syncwarp();
                    if (lane == 0) mbar_arrive(empty0 + 8 * st);
                    float mine = (c & 4) ? s1 : s0;
                    const float other = (c & 4) ? s0 : s1;
                    mine += __shfl_xor_sync(0xffffffffu, other, 4);
                    mine += __shfl_xor_sync(0xffffffffu, mine, 2);
                    mine += __shfl_xor_sync(0xffffffffu, mine, 1);
                    if ((c & 3) == 0) sm.sc[j][warp * 8 + c + g] = bfr(bfr(mine) * scale);
                }
            }
            bar_sync(kBarCons, 256);
            {
                float4 sv = *reinterpret_cast<const float4*>(&sm.sc[0][tid * 4]);
                float m = fmaxf(fmaxf(sv.x, sv.y), fmaxf(sv.z, sv.w));
#pragma unroll
                for (int o = 8; o > 0; o >>= 1) m = fmaxf(m, __shfl_xor_sync(0xffffffffu, m, o));
                m = fmaxf(m, -3.0e38f);
                sv.x = __expf(sv.x - m); sv.y = __expf(sv.y - m); sv.z = __expf(sv.z - m); sv.w = __expf(sv.w - m);
                *reinterpret_cast<uint2*>(&sm.rowc[tid * 4]) = make_uint2(pack_bf16(sv.x, sv.y), pack_bf16(sv.z, sv.w));
                float l = (sv.x + sv.y) + (sv.z + sv.w);
#pragma unroll
                for (int o = 8; o > 0; o >>= 1) l += __shfl_xor_sync(0xffffffffu, l, o);
                if ((lane & 15) == 0) { sm.stat[(tid >> 4) * 2] = m; sm.stat[(tid >> 4) * 2 + 1] = l; }
            }
        }

        if (warp < 5) {
            const uint32_t* cw = reinterpret_cast<const uint32_t*>(sm.coef);
            int tqp = tq;
            asm volatile("" : "+r"(tqp));
            const bool q0 = tqp == 0, q1 = tqp == 1;
            float4* slot = out_slot(p.g, (((cta & 1) * 5 + warp) * 8 + mg) * 3 + tq);
            __nv_bfloat16* o = p.out + ((cta & 1) * 5 + warp) * 64 + tq * 24 + mg;
            float d[4][4];
            uint32_t off[4], w0[8][4], w1[8][4];
            float f0, f1, f2;
#pragma unroll
            for (int i = 0; i < 4; i++) off[i] = lk * 128 + ((((2 * i + ((lane >> 3) & 1)) ^ lk) & 7) << 4);
            {
                const uint32_t b0 = cw[48 + tq], b1 = cw[52 + tq], b2 = cw[56 + tq], b3 = cw[60 + tq];
                const float gb = sm.gate[1];
                const uint32_t a = ring0 + (kTD % kStages) * kTileB + warp * kFC * 128;
                mbar_wait(full0 + 8 * (kTD % kStages), (kTD / kStages) & 1);
#pragma unroll
                for (int i = 0; i < 4; i++) {
                    ldsm4t(w0[i], a + off[i]);
                    ldsm4t(w0[4 + i], a + off[i] + (lane < 16 ? 16 : 8) * 128);
                }
#pragma unroll
                for (int i = 0; i < 4; i++) {
                    d[i][0] = d[i][1] = d[i][2] = d[i][3] = 0.f;
                    mma16816(d[i], w0[i], b0, b1);
                    mma16816(d[i], w0[4 + i], b2, b3);
                }
                f0 = gb * fsel(q0, d[0][0], fsel(q1, d[1][2], d[3][0]));
                f1 = gb * fsel(q0, d[0][2], fsel(q1, d[2][0], d[3][2]));
                f2 = gb * fsel(q0, d[1][0], d[2][2]);
            }
#pragma unroll
            for (int i = 0; i < 4; i++) off[i] += ring0 + warp * 32 * 128;
            asm volatile("" : "+r"(off[0]), "+r"(off[1]), "+r"(off[2]), "+r"(off[3]));
            mbar_wait(full0 + 8 * (kTO % kStages), (kTO / kStages) & 1);
#pragma unroll
            for (int i = 0; i < 8; i++) ldsm4t(w0[i], off[i & 3] + (kTO % kStages) * kTileB + (i >> 2) * 2048);
            uint32_t b[12];
            float ga = sm.gate[0];
#pragma unroll
            for (int i = 0; i < 4; i++) d[i][0] = d[i][1] = d[i][2] = d[i][3] = 0.f;
            const bool early = __all_sync(0xffffffffu, mbar_test(s2u(&sm.coef_ready), 0));
            if (early) {
#pragma unroll
                for (int j = 0; j < 12; j++) b[j] = cw[j * 4 + tq];
#pragma unroll
                for (int i = 0; i < 8; i++) mma16816(d[i & 3], w0[i], b[(i >> 2) * 2], b[(i >> 2) * 2 + 1]);
            }
            asm volatile("" : "+l"(slot), "+l"(o), "+f"(ga), "+f"(f0), "+f"(f1), "+f"(f2));
            mbar_wait(full0 + 8 * ((kTO + 1) % kStages), ((kTO + 1) / kStages) & 1);
#pragma unroll
            for (int i = 0; i < 8; i++) ldsm4t(w1[i], off[i & 3] + ((kTO + 1) % kStages) * kTileB + (i >> 2) * 2048);
            if (!early) {
                mbar_wait(s2u(&sm.coef_ready), 0);
#pragma unroll
                for (int j = 0; j < 12; j++) b[j] = cw[j * 4 + tq];
#pragma unroll
                for (int i = 0; i < 8; i++) mma16816(d[i & 3], w0[i], b[(i >> 2) * 2], b[(i >> 2) * 2 + 1]);
            }
#pragma unroll
            for (int i = 0; i < 8; i++) mma16816(d[i & 3], w1[i], b[4 + (i >> 2) * 2], b[5 + (i >> 2) * 2]);
            mbar_wait(full0 + 8 * ((kTO + 2) % kStages), ((kTO + 2) / kStages) & 1);
#pragma unroll
            for (int i = 0; i < 8; i++) ldsm4t(w0[i], off[i & 3] + ((kTO + 2) % kStages) * kTileB + (i >> 2) * 2048);
#pragma unroll
            for (int i = 0; i < 8; i++) mma16816(d[i & 3], w0[i], b[8 + (i >> 2) * 2], b[9 + (i >> 2) * 2]);
            const float v0 = fmaf(ga, fsel(q0, d[0][0], fsel(q1, d[1][2], d[3][0])), f0);
            const float v1 = fmaf(ga, fsel(q0, d[0][2], fsel(q1, d[2][0], d[3][2])), f1);
            const float v2 = fmaf(ga, fsel(q0, d[1][0], d[2][2]), f2);
            if (tqp < 3) {
                const float4 old = atom_add4(slot, v0, v1, v2, 1.0f);
                if (old.w == (float)(kCTAs / 2 - 1)) {
                    st_bf16(o, old.x + v0);
                    st_bf16(o + 8, old.y + v1);
                    if (tqp < 2) st_bf16(o + 16, old.z + v2);
                }
            }
        }
        if (warp < 6) return;
    }

    {
        const int tt = warp == kCW + 1 ? 64 + lane : tid - 192;
        const int half = (cta >> 1) & 1;
        bar_sync(kBarTeam, 96);
        mbar_wait(s2u(&sm.go[1]), 0);
        if (hl >= kGH - kLate) {
            if (tt < kOC / 2) {
                float4* slot = late_slot(p.g, ((cta >> 6) * kLate + hl - (kGH - kLate)) * kOSlots + half * (kOC / 2) + tt);
                float4 r;
                unsigned n = 0;
                do { r = atom_add4(slot, 0.f, 0.f, 0.f, 0.f); if (++n > kSpinLimit) __trap(); } while (r.w != (float)kGrp);
                const int d = (tt >> 4) * 32 + (tt & 1) * 16 + ((tt >> 1) & 7);
                sm.coef[d] = __float2bfloat16_rn(r.x);
                sm.coef[d + 8] = __float2bfloat16_rn(r.y);
            }
        } else {
            const int c = tt % 24, sg = tt / 24;
            const unsigned* const ps[1] = {&p.g->omail[hl][cta0 + sg][half * kOC + c * 4]};
            Chunk r[16];
            mail_gather<16>(ps, 4 * kDh, tag, r);
            float4 acc = make_float4(0.f, 0.f, 0.f, 0.f);
#pragma unroll
            for (int k = 0; k < 16; k++) {
                const float w = sm.wgt[sg + 4 * k];
                acc.x = fmaf(w, r[k].v(0), acc.x); acc.y = fmaf(w, r[k].v(1), acc.y);
                acc.z = fmaf(w, r[k].v(2), acc.z); acc.w = fmaf(w, r[k].v(3), acc.w);
            }
            *reinterpret_cast<float4*>(&sm.part[sg][c * 4]) = acc;
            bar_sync(kBarTeam, 96);
            if (tt < kOC / 2) {
                const float2 a = *reinterpret_cast<const float2*>(&sm.part[0][tt * 2]), b = *reinterpret_cast<const float2*>(&sm.part[1][tt * 2]);
                const float2 e = *reinterpret_cast<const float2*>(&sm.part[2][tt * 2]), f = *reinterpret_cast<const float2*>(&sm.part[3][tt * 2]);
                reinterpret_cast<uint32_t*>(sm.coef)[tt] = pack_bf16((a.x + b.x) + (e.x + f.x), (a.y + b.y) + (e.y + f.y));
            }
        }
        __syncwarp();
        if (tt < 64 && lane == 0) mbar_arrive(s2u(&sm.coef_ready));
    }
}

__device__ float g_fb[2 * kH * kDh + kF];
__device__ __forceinline__ float ldbf(const void* p, size_t i) { return __bfloat162float(reinterpret_cast<const __nv_bfloat16*>(p)[i]); }
__global__ void fb_proj(const void* x, const void* wq, const void* wg, const void* wu) {
    const int n = blockIdx.x * blockDim.x + threadIdx.x;
    if (n < kH * kDh) {
        float a = 0.f;
        for (int k = 0; k < kD; k++) a = fmaf(ldbf(x, k), ldbf(wq, (size_t)k * kH * kDh + n), a);
        g_fb[n] = bfr(a);
    } else if (n < kH * kDh + kF) {
        const int f = n - kH * kDh;
        float a = 0.f, b = 0.f;
        for (int k = 0; k < kD; k++) { a = fmaf(ldbf(x, k), ldbf(wg, (size_t)k * kF + f), a); b = fmaf(ldbf(x, k), ldbf(wu, (size_t)k * kF + f), b); }
        a = bfr(a);
        g_fb[2 * kH * kDh + f] = bfr((a > 0.f ? a : a * 0.f) * bfr(b));
    }
}
__global__ void fb_attn(const void* kc, const void* vc) {
    __shared__ float sc[kW], red[kDh];
    const int h = blockIdx.x, t = threadIdx.x;
    const size_t base = ((size_t)h * kSk + kSk - kW) * kDh;
    float m = -INFINITY, l = 0.f, o = 0.f;
    for (int k = t; k < kW; k += kDh) {
        float a = 0.f;
        for (int d = 0; d < kDh; d++) a = fmaf(g_fb[h * kDh + d], ldbf(kc, base + (size_t)k * kDh + d), a);
        sc[k] = bfr(bfr(a) * 0.07216878364870322f);
        m = fmaxf(m, sc[k]);
    }
    red[t] = m;
    __syncthreads();
    for (int i = 0; i < kDh; i++) m = fmaxf(m, red[i]);
    for (int k = 0; k < kW; k++) {
        const float e = __expf(sc[k] - m);
        l += e;
        o = fmaf(e, ldbf(vc, base + (size_t)k * kDh + t), o);
    }
    g_fb[kH * kDh + h * kDh + t] = bfr(o / l);
}
__global__ void fb_out(const void* x, const void* gw, const void* wo, const void* wd, __nv_bfloat16* out) {
    const int n = blockIdx.x * blockDim.x + threadIdx.x;
    float z = 0.f, a = 0.f, b = 0.f;
    for (int k = 0; k < kD; k++) z += bfr(ldbf(x, k) * ldbf(gw, k));
    const float g = bfr(1.0f / (1.0f + __expf(-bfr(z))));
    for (int k = 0; k < kH * kDh; k++) a = fmaf(g_fb[kH * kDh + k], ldbf(wo, (size_t)k * kD + n), a);
    for (int k = 0; k < kF; k++) b = fmaf(g_fb[2 * kH * kDh + k], ldbf(wd, (size_t)k * kD + n), b);
    out[n] = __float2bfloat16_rn(g * a + bfr(1.0f - g) * b);
}

typedef CUresult (*EncodeFn)(CUtensorMap*, CUtensorMapDataType, cuuint32_t, void*, const cuuint64_t*, const cuuint64_t*,
                             const cuuint32_t*, const cuuint32_t*, CUtensorMapInterleave, CUtensorMapSwizzle,
                             CUtensorMapL2promotion, CUtensorMapFloatOOBfill);

void make_map(EncodeFn fn, CUtensorMap* m, void* base, int rows, int cols, int box_rows) {
    const cuuint64_t dims[3] = {64, (cuuint64_t)(cols / 64), (cuuint64_t)rows};
    const cuuint64_t strides[2] = {128, (cuuint64_t)cols * 2};
    const cuuint32_t box[3] = {64, 3, (cuuint32_t)box_rows};
    const cuuint32_t estr[3] = {1, 1, 1};
    fn(m, CU_TENSOR_MAP_DATA_TYPE_BFLOAT16, 3, base, dims, strides, box, estr, CU_TENSOR_MAP_INTERLEAVE_NONE,
       CU_TENSOR_MAP_SWIZZLE_128B, CU_TENSOR_MAP_L2_PROMOTION_NONE, CU_TENSOR_MAP_FLOAT_OOB_FILL_NONE);
}
void make_map_out(EncodeFn fn, CUtensorMap* m, void* base, int rows, int box_rows) {
    const cuuint64_t dims[3] = {64, (cuuint64_t)rows, (cuuint64_t)(kD / 64)};
    const cuuint64_t strides[2] = {(cuuint64_t)kOutRowB, 128};
    const cuuint32_t box[3] = {64, (cuuint32_t)box_rows, 5};
    const cuuint32_t estr[3] = {1, 1, 1};
    fn(m, CU_TENSOR_MAP_DATA_TYPE_BFLOAT16, 3, base, dims, strides, box, estr, CU_TENSOR_MAP_INTERLEAVE_NONE,
       CU_TENSOR_MAP_SWIZZLE_128B, CU_TENSOR_MAP_L2_PROMOTION_NONE, CU_TENSOR_MAP_FLOAT_OOB_FILL_NONE);
}

}

extern "C" void kernel_launch(void* const* d_in, const int* in_sizes, int n_in, void* d_out, int out_size) {
    (void)in_sizes; (void)n_in; (void)out_size;
    static EncodeFn encode = nullptr;
    static void* scratch = nullptr;
    static int resident = -1;
    if (resident < 0) {
        cudaGetSymbolAddress(&scratch, g_scratch);
        void* fn = nullptr;
        cudaDriverEntryPointQueryResult qr;
        cudaGetDriverEntryPoint("cuTensorMapEncodeTiled", &fn, cudaEnableDefault, &qr);
        encode = (EncodeFn)fn;
        cudaFuncSetAttribute(fused_decode_kernel, cudaFuncAttributeMaxDynamicSharedMemorySize, (int)sizeof(Smem));
        int dev = 0, sms = 0, per_sm = 0;
        cudaGetDevice(&dev);
        cudaDeviceGetAttribute(&sms, cudaDevAttrMultiProcessorCount, dev);
        cudaOccupancyMaxActiveBlocksPerMultiprocessor(&per_sm, fused_decode_kernel, kThreads, sizeof(Smem));
        resident = sms * per_sm;
    }
    if (resident < kCTAs || !encode) {
        fb_proj<<<(kH * kDh + kF) / 128, 128, 0, cudaStreamPerThread>>>(d_in[0], d_in[3], d_in[6], d_in[7]);
        fb_attn<<<kH, kDh, 0, cudaStreamPerThread>>>(d_in[1], d_in[2]);
        fb_out<<<kD / 32, 32, 0, cudaStreamPerThread>>>(d_in[0], d_in[9], d_in[4], d_in[8], (__nv_bfloat16*)d_out);
        return;
    }
    Params p;
    p.x = (const __nv_bfloat16*)d_in[0];
    p.k = (const unsigned char*)d_in[1];
    p.gate_w = (const __nv_bfloat16*)d_in[9];
    p.out = (__nv_bfloat16*)d_out;
    p.g = (Scratch*)scratch;
    make_map(encode, &p.tq, d_in[3], kD, kH * kDh, 32);
    make_map(encode, &p.tg, d_in[6], kD, kF, 16);
    make_map(encode, &p.tu, d_in[7], kD, kF, 16);
    make_map(encode, &p.tv, d_in[2], kH * kSk, kDh, kTileKeys);
    make_map_out(encode, &p.td, d_in[8], kF, kFC);
    make_map_out(encode, &p.to, d_in[4], kH * kDh, 32);
    cudaLaunchConfig_t cfg = {};
    cfg.gridDim = dim3(kCTAs);
    cfg.blockDim = dim3(kThreads);
    cfg.dynamicSmemBytes = sizeof(Smem);
    cfg.stream = cudaStreamPerThread;
    cudaLaunchAttribute attr;
    attr.id = cudaLaunchAttributeCooperative;
    attr.val.cooperative = 1;
    cfg.attrs = &attr;
    cfg.numAttrs = 1;
    cudaLaunchKernelEx(&cfg, fused_decode_kernel, (const unsigned char*)d_in[3], p);
}
```
